```python
import torch

def _softmax(x, axis=-1):
    return torch.softmax(x, dim=axis)
def _gelu(x):
    return torch.nn.functional.gelu(x, approximate="tanh")
def _silu(x):
    return torch.nn.functional.silu(x)
def _sigmoid(x):
    return torch.sigmoid(x)
def _layernorm(x, axis=-1, eps=1e-5):
    m = x.mean(dim=axis, keepdim=True)
    v = x.var(dim=axis, keepdim=True, unbiased=False)
    return (x - m) / torch.sqrt(v + eps)
def _scatter_add(tgt, idx, src, axis=0):
    return tgt.clone().index_add_(axis, idx, src)
def _segment_sum(src, seg, n):
    out = torch.zeros((n,) + src.shape[1:], dtype=src.dtype)
    return out.index_add_(0, seg, src)
def _pad(x, pw):
    flat = tuple(v for pair in reversed(pw) for v in pair)
    return torch.nn.functional.pad(x, flat)

kernel_name = 'recurrent_scan__ssm_conv_s4__mixer_channel_mlp__prompt'

def setup_inputs():

    _w = (lambda a: (lambda t: t.to(torch.bfloat16) if t.is_floating_point() else t)(torch.as_tensor(a)))
    def _A_setup():
        B, L, D, N = 1, 2048, 448, 256
        A_re = -(lambda _x: torch.exp(torch.as_tensor(_x)))((lambda *s: torch.randn(*s, dtype=torch.bfloat16) * 3.2)(D, N))
        A_im = torch.pi * (lambda *s: torch.randn(*s, dtype=torch.bfloat16) * 0.2)(D, N)
        B_re = (lambda *s: torch.randn(*s, dtype=torch.bfloat16) * 0.2)(D, N)
        B_im = (lambda *s: torch.randn(*s, dtype=torch.bfloat16) * 0.2)(D, N)
        C_re = (lambda *s: torch.randn(*s, dtype=torch.bfloat16) * 0.2)(D, N)
        C_im = (lambda *s: torch.randn(*s, dtype=torch.bfloat16) * 0.2)(D, N)
        log_dt = (lambda *s: torch.randn(*s, dtype=torch.bfloat16) * 0.2)(D) * 0.5 - 4.0
        Dskip = (lambda *s: torch.randn(*s, dtype=torch.bfloat16) * 0.2)(D)
        return {
            "u": _w((lambda *s: torch.randn(*s, dtype=torch.bfloat16) * 0.05)(B, L, D)),
            "A_re": _w(A_re),
            "A_im": _w(A_im),
            "B_re": _w(B_re),
            "B_im": _w(B_im),
            "C_re": _w(C_re),
            "C_im": _w(C_im),
            "log_dt": _w(log_dt),
            "Dskip": _w(Dskip),
        }
    _A_in = _A_setup()

    def _B_setup():
        B, S, D, F = 1, 2048, 448, 1792
        return {
            "x": _w((lambda *s: torch.randn(*s, dtype=torch.bfloat16) * 0.05)(B, S, D)),
            "w1": _w((lambda *s: torch.randn(*s, dtype=torch.bfloat16) * 3.2)(D, F) * (D ** -0.5)),
            "b1": _w((lambda *s: torch.randn(*s, dtype=torch.bfloat16) * 1.6)(F)),
            "w2": _w((lambda *s: torch.randn(*s, dtype=torch.bfloat16) * 0.1)(F, D) * (F ** -0.5)),
            "b2": _w((lambda *s: torch.randn(*s, dtype=torch.bfloat16) * 0.2)(D)),
        }
    _B_in = _B_setup()

    return {
        "A_u": _A_in["u"],
        "A_A_re": _A_in["A_re"],
        "A_A_im": _A_in["A_im"],
        "A_B_re": _A_in["B_re"],
        "A_B_im": _A_in["B_im"],
        "A_C_re": _A_in["C_re"],
        "A_C_im": _A_in["C_im"],
        "A_log_dt": _A_in["log_dt"],
        "A_Dskip": _A_in["Dskip"],
        "B_x": _B_in["x"],
        "B_w1": _B_in["w1"],
        "B_b1": _B_in["b1"],
        "B_w2": _B_in["w2"],
        "B_b2": _B_in["b2"],
    }

def reference(A_u, A_A_re, A_A_im, A_B_re, A_B_im, A_C_re, A_C_im, A_log_dt, A_Dskip, B_x, B_w1, B_b1, B_w2, B_b2):
    def _A_ref(u, A_re, A_im, B_re, B_im, C_re, C_im, log_dt, Dskip):
        Bsz, L, D = u.shape
        dt = torch.exp(log_dt)[:, None]
        A = A_re + 1j * A_im
        Bc = B_re + 1j * B_im
        Cc = C_re + 1j * C_im
        logdA = dt * A
        dB = dt * Bc
        l = (lambda x, dt: x.to(dt))(torch.arange(L), A_re.dtype)
        P = torch.exp(logdA[:, :, None] * l[None, None, :])
        K = torch.einsum("dn,dnl,dn->dl", Cc, P, dB).real
        L2 = 2 * L
        Kp = _pad(K, ((0, 0), (0, L)))
        up = (lambda x, *d: x.permute(*d))(u, 0, 2, 1)
        up = _pad(up, ((0, 0), (0, 0), (0, L)))
        Kf = (lambda x, axes=(-2,-1): torch.fft.rfft2(x.float(), dim=axes))(Kp[:, None, :], axes=(-2, -1))
        Uf = (lambda x, axes=(-2,-1): torch.fft.rfft2(x.float(), dim=axes))(up[:, :, None, :], axes=(-2, -1))
        Yf = Uf * Kf[None, :, :, :]
        y = (lambda x, s, axes=(-2,-1): torch.fft.irfft2(x, s=s, dim=axes).to(torch.bfloat16))(Yf, (1, L2), axes=(-2, -1))[:, :, 0, :L]
        y = (lambda x, *d: x.permute(*d))(y, 0, 2, 1) + u * Dskip[None, None, :]
        return y

    def _B_ref(x, w1, b1, w2, b2):
        y = _layernorm(x, axis=-1)
        h = _gelu(torch.einsum("bsd,df->bsf", y, w1) + b1)
        return torch.einsum("bsf,fd->bsd", h, w2) + b2

    x = A_u
    xn = _layernorm(x, axis=-1)
    s = _A_ref(xn, A_A_re, A_A_im, A_B_re, A_B_im, A_C_re, A_C_im, A_log_dt, A_Dskip)
    g = _silu(_B_ref(xn, B_w1, B_b1, B_w2, B_b2))
    return x + s * g
```

```cpp
#include <cuda_runtime.h>
#include <cuda_bf16.h>
#include <cuda.h>
#include <stdint.h>

namespace {

constexpr int LSEQ = 2048, DM = 448, FF = 1792;
constexpr int NMLP = 112, NEXP = 56;
constexpr int SLOT = 16384, RING_BYTES = SLOT * 10;
constexpr int BX_OFF = 9 * SLOT, AX_OFF = BX_OFF + 8192;
constexpr int TP_OFF = 0, T2A_OFF = 2192, TT_BYTES = 2112, T3_OFF = T2A_OFF + 2 * TT_BYTES;
constexpr int V2_OFF = 8064 + 64, V3_OFF = 8064 + 6208, CH_BYTES = 18432;
constexpr int STG_BYTES = 28672, CA_BYTES = 2 * STG_BYTES;
constexpr int LIN_OFF = 2 * CH_BYTES, LIN_BYTES = 2720;
constexpr int U_COPY = 138 * 32, U_BYTES = 4608, U3_OFF = LIN_OFF + 5632, F3_OFF = U3_OFF + U_BYTES;
constexpr int UP_OFF = RING_BYTES + CA_BYTES;
constexpr int BAR_OFF = UP_OFF + 2 * U_BYTES;
constexpr int B_F1 = 0, B_F2 = 7, B_PB = 14, B_S = 20, B_X = 21, B_EPOCH = 22, B_U = 23, B_U3 = 25, B_CONST = 27, B_E1 = 28, B_SENT = 35, NBAR = 41;
constexpr int CNT_OFF = BAR_OFF + 352;
constexpr int DBG_OFF = CNT_OFF + 32;
constexpr int SMEM_BYTES = DBG_OFF + 128 + 768;
constexpr int SPIN_LIMIT = 1 << 20, POLL_LIMIT = 1 << 17;
#define HD0 600
#define HD1 300
#define DELAY0 0
#define NPRE 2
#define HD2 100
#define CSW 4
#define STAGGER 0
#define START_GAP 0

struct Scratch {
  uint4 xT[DM * 276];
  uint4 ab[LSEQ];
  float cs[4 * FF];
  unsigned int flag[64];
  uint32_t hintp[16 * 7 * 64];
  uint32_t hints[DM * 4];
  uint4 kexp[(2 * NEXP + 32) * 192];
  uint2 s[16 * DM * 32];
  uint4 part[16 * 7 * 6 * 1024];
};
__device__ __align__(1024) Scratch g_scr;

struct Params {
  const __nv_bfloat16 *x, *w1, *Are, *Aim, *Bre, *Bim, *Cre, *Cim, *logdt, *Dskip, *b1, *b2, *w2;
  Scratch* scr;
};

#define TS(i)
#define TSX(i)
#define TS_FLUSH()

__device__ __forceinline__ void wg_ss48_pos(float* d, uint32_t da, uint32_t db) {
  asm volatile("{\n.reg .b64 a,b;\nmov.b64 a, {%24, 0x40};\nmov.b64 b, {%25, 0x40};\n"
      "wgmma.mma_async.sync.aligned.m64n48k16.f32.f16.f16 {"
      "%0,%1,%2,%3,%4,%5,%6,%7,%8,%9,%10,%11,%12,%13,%14,%15,%16,%17,%18,%19,%20,%21,%22,%23}, a, b, 1, 1, 1, 1, 1;\n}"
      : "+f"(d[0]),"+f"(d[1]),"+f"(d[2]),"+f"(d[3]),"+f"(d[4]),"+f"(d[5]),"+f"(d[6]),"+f"(d[7]),"+f"(d[8]),"+f"(d[9]),"+f"(d[10]),"+f"(d[11]),"+f"(d[12]),
      "+f"(d[13]),"+f"(d[14]),"+f"(d[15]),"+f"(d[16]),"+f"(d[17]),"+f"(d[18]),"+f"(d[19]),"+f"(d[20]),"+f"(d[21]),"+f"(d[22]),"+f"(d[23])
      : "r"(da), "r"(db));
}
__device__ __forceinline__ void wg_ss48_neg(float* d, uint32_t da, uint32_t db) {
  asm volatile("{\n.reg .b64 a,b;\nmov.b64 a, {%24, 0x40};\nmov.b64 b, {%25, 0x40};\n"
      "wgmma.mma_async.sync.aligned.m64n48k16.f32.f16.f16 {"
      "%0,%1,%2,%3,%4,%5,%6,%7,%8,%9,%10,%11,%12,%13,%14,%15,%16,%17,%18,%19,%20,%21,%22,%23}, a, b, 1, -1, 1, 1, 1;\n}"
      : "+f"(d[0]),"+f"(d[1]),"+f"(d[2]),"+f"(d[3]),"+f"(d[4]),"+f"(d[5]),"+f"(d[6]),"+f"(d[7]),"+f"(d[8]),"+f"(d[9]),"+f"(d[10]),"+f"(d[11]),"+f"(d[12]),
      "+f"(d[13]),"+f"(d[14]),"+f"(d[15]),"+f"(d[16]),"+f"(d[17]),"+f"(d[18]),"+f"(d[19]),"+f"(d[20]),"+f"(d[21]),"+f"(d[22]),"+f"(d[23])
      : "r"(da), "r"(db));
}
__device__ __forceinline__ void wg_rs128_t(float* d, uint32_t a0, uint32_t a1, uint32_t a2, uint32_t a3, uint32_t db) {
  asm volatile("{\n.reg .b64 b;\nmov.b64 b, {%68, 0x40000040};\n"
      "wgmma.mma_async.sync.aligned.m64n128k16.f32.bf16.bf16 {"
      "%0,%1,%2,%3,%4,%5,%6,%7,%8,%9,%10,%11,%12,%13,%14,%15,%16,%17,%18,%19,%20,%21,%22,%23,%24,%25,%26,%27,%28,%29,%30,%31,%32,%33,%34,%35,%36,%37,%38,%39,"
      "%40,%41,%42,%43,%44,%45,%46,%47,%48,%49,%50,%51,%52,%53,%54,%55,%56,%57,%58,%59,%60,%61,%62,%63}, {%64,%65,%66,%67}, b, 1, 1, 1, 1;\n}"
      : "+f"(d[0]),"+f"(d[1]),"+f"(d[2]),"+f"(d[3]),"+f"(d[4]),"+f"(d[5]),"+f"(d[6]),"+f"(d[7]),"+f"(d[8]),"+f"(d[9]),"+f"(d[10]),"+f"(d[11]),"+f"(d[12]),
      "+f"(d[13]),"+f"(d[14]),"+f"(d[15]),"+f"(d[16]),"+f"(d[17]),"+f"(d[18]),"+f"(d[19]),"+f"(d[20]),"+f"(d[21]),"+f"(d[22]),"+f"(d[23]),"+f"(d[24]),
      "+f"(d[25]),"+f"(d[26]),"+f"(d[27]),"+f"(d[28]),"+f"(d[29]),"+f"(d[30]),"+f"(d[31]),"+f"(d[32]),"+f"(d[33]),"+f"(d[34]),"+f"(d[35]),"+f"(d[36]),
      "+f"(d[37]),"+f"(d[38]),"+f"(d[39]),"+f"(d[40]),"+f"(d[41]),"+f"(d[42]),"+f"(d[43]),"+f"(d[44]),"+f"(d[45]),"+f"(d[46]),"+f"(d[47]),"+f"(d[48]),
      "+f"(d[49]),"+f"(d[50]),"+f"(d[51]),"+f"(d[52]),"+f"(d[53]),"+f"(d[54]),"+f"(d[55]),"+f"(d[56]),"+f"(d[57]),"+f"(d[58]),"+f"(d[59]),"+f"(d[60]),
      "+f"(d[61]),"+f"(d[62]),"+f"(d[63])
      : "r"(a0), "r"(a1), "r"(a2), "r"(a3), "r"(db));
}
__device__ __forceinline__ void wg_rs64_t(float* d, uint32_t a0, uint32_t a1, uint32_t a2, uint32_t a3, uint32_t db) {
  asm volatile("{\n.reg .b64 b;\nmov.b64 b, {%36, 0x40000040};\n"
      "wgmma.mma_async.sync.aligned.m64n64k16.f32.bf16.bf16 {"
      "%0,%1,%2,%3,%4,%5,%6,%7,%8,%9,%10,%11,%12,%13,%14,%15,%16,%17,%18,%19,%20,%21,%22,%23,%24,%25,%26,%27,%28,%29,%30,%31}, {%32,%33,%34,%35}, b, 1, 1, 1, 1;\n}"
      : "+f"(d[0]),"+f"(d[1]),"+f"(d[2]),"+f"(d[3]),"+f"(d[4]),"+f"(d[5]),"+f"(d[6]),"+f"(d[7]),"+f"(d[8]),"+f"(d[9]),"+f"(d[10]),"+f"(d[11]),"+f"(d[12]),
      "+f"(d[13]),"+f"(d[14]),"+f"(d[15]),"+f"(d[16]),"+f"(d[17]),"+f"(d[18]),"+f"(d[19]),"+f"(d[20]),"+f"(d[21]),"+f"(d[22]),"+f"(d[23]),"+f"(d[24]),
      "+f"(d[25]),"+f"(d[26]),"+f"(d[27]),"+f"(d[28]),"+f"(d[29]),"+f"(d[30]),"+f"(d[31])
      : "r"(a0), "r"(a1), "r"(a2), "r"(a3), "r"(db));
}
__device__ __forceinline__ void wg_rs64_t_init(float* d, uint32_t a0, uint32_t a1, uint32_t a2, uint32_t a3, uint32_t db) {
  asm volatile("{\n.reg .b64 b;\nmov.b64 b, {%36, 0x40000040};\n"
      "wgmma.mma_async.sync.aligned.m64n64k16.f32.bf16.bf16 {"
      "%0,%1,%2,%3,%4,%5,%6,%7,%8,%9,%10,%11,%12,%13,%14,%15,%16,%17,%18,%19,%20,%21,%22,%23,%24,%25,%26,%27,%28,%29,%30,%31}, {%32,%33,%34,%35}, b, 0, 1, 1, 1;\n}"
      : "=f"(d[0]),"=f"(d[1]),"=f"(d[2]),"=f"(d[3]),"=f"(d[4]),"=f"(d[5]),"=f"(d[6]),"=f"(d[7]),"=f"(d[8]),"=f"(d[9]),"=f"(d[10]),"=f"(d[11]),"=f"(d[12]),
      "=f"(d[13]),"=f"(d[14]),"=f"(d[15]),"=f"(d[16]),"=f"(d[17]),"=f"(d[18]),"=f"(d[19]),"=f"(d[20]),"=f"(d[21]),"=f"(d[22]),"=f"(d[23]),"=f"(d[24]),
      "=f"(d[25]),"=f"(d[26]),"=f"(d[27]),"=f"(d[28]),"=f"(d[29]),"=f"(d[30]),"=f"(d[31])
      : "r"(a0), "r"(a1), "r"(a2), "r"(a3), "r"(db));
}
__device__ __forceinline__ void wg_rs96(float* d, uint32_t a0, uint32_t a1, uint32_t a2, uint32_t a3, uint32_t db) {
  asm volatile("{\n.reg .b64 b;\nmov.b64 b, {%52, 0x8};\n"
      "wgmma.mma_async.sync.aligned.m64n96k16.f32.bf16.bf16 {"
      "%0,%1,%2,%3,%4,%5,%6,%7,%8,%9,%10,%11,%12,%13,%14,%15,%16,%17,%18,%19,%20,%21,%22,%23,%24,%25,%26,%27,%28,%29,%30,%31,%32,%33,%34,%35,%36,%37,%38,%39,"
      "%40,%41,%42,%43,%44,%45,%46,%47}, {%48,%49,%50,%51}, b, 1, 1, 1, 0;\n}"
      : "+f"(d[0]),"+f"(d[1]),"+f"(d[2]),"+f"(d[3]),"+f"(d[4]),"+f"(d[5]),"+f"(d[6]),"+f"(d[7]),"+f"(d[8]),"+f"(d[9]),"+f"(d[10]),"+f"(d[11]),"+f"(d[12]),
      "+f"(d[13]),"+f"(d[14]),"+f"(d[15]),"+f"(d[16]),"+f"(d[17]),"+f"(d[18]),"+f"(d[19]),"+f"(d[20]),"+f"(d[21]),"+f"(d[22]),"+f"(d[23]),"+f"(d[24]),
      "+f"(d[25]),"+f"(d[26]),"+f"(d[27]),"+f"(d[28]),"+f"(d[29]),"+f"(d[30]),"+f"(d[31]),"+f"(d[32]),"+f"(d[33]),"+f"(d[34]),"+f"(d[35]),"+f"(d[36]),
      "+f"(d[37]),"+f"(d[38]),"+f"(d[39]),"+f"(d[40]),"+f"(d[41]),"+f"(d[42]),"+f"(d[43]),"+f"(d[44]),"+f"(d[45]),"+f"(d[46]),"+f"(d[47])
      : "r"(a0), "r"(a1), "r"(a2), "r"(a3), "r"(db));
}
__device__ __forceinline__ void wg_rs64(float* d, uint32_t a0, uint32_t a1, uint32_t a2, uint32_t a3, uint32_t db) {
  asm volatile("{\n.reg .b64 b;\nmov.b64 b, {%36, 0x8};\n"
      "wgmma.mma_async.sync.aligned.m64n64k16.f32.bf16.bf16 {"
      "%0,%1,%2,%3,%4,%5,%6,%7,%8,%9,%10,%11,%12,%13,%14,%15,%16,%17,%18,%19,%20,%21,%22,%23,%24,%25,%26,%27,%28,%29,%30,%31}, {%32,%33,%34,%35}, b, 1, 1, 1, 0;\n}"
      : "+f"(d[0]),"+f"(d[1]),"+f"(d[2]),"+f"(d[3]),"+f"(d[4]),"+f"(d[5]),"+f"(d[6]),"+f"(d[7]),"+f"(d[8]),"+f"(d[9]),"+f"(d[10]),"+f"(d[11]),"+f"(d[12]),
      "+f"(d[13]),"+f"(d[14]),"+f"(d[15]),"+f"(d[16]),"+f"(d[17]),"+f"(d[18]),"+f"(d[19]),"+f"(d[20]),"+f"(d[21]),"+f"(d[22]),"+f"(d[23]),"+f"(d[24]),
      "+f"(d[25]),"+f"(d[26]),"+f"(d[27]),"+f"(d[28]),"+f"(d[29]),"+f"(d[30]),"+f"(d[31])
      : "r"(a0), "r"(a1), "r"(a2), "r"(a3), "r"(db));
}
__device__ __forceinline__ void wg_rs32(float* d, uint32_t a0, uint32_t a1, uint32_t a2, uint32_t a3, uint32_t db) {
  asm volatile("{\n.reg .b64 b;\nmov.b64 b, {%20, 0x8};\n"
      "wgmma.mma_async.sync.aligned.m64n32k16.f32.bf16.bf16 {"
      "%0,%1,%2,%3,%4,%5,%6,%7,%8,%9,%10,%11,%12,%13,%14,%15}, {%16,%17,%18,%19}, b, 1, 1, 1, 0;\n}"
      : "+f"(d[0]),"+f"(d[1]),"+f"(d[2]),"+f"(d[3]),"+f"(d[4]),"+f"(d[5]),"+f"(d[6]),"+f"(d[7]),"+f"(d[8]),"+f"(d[9]),"+f"(d[10]),"+f"(d[11]),"+f"(d[12]),
      "+f"(d[13]),"+f"(d[14]),"+f"(d[15])
      : "r"(a0), "r"(a1), "r"(a2), "r"(a3), "r"(db));
}
__device__ __forceinline__ void wg_rs32_init(float* d, uint32_t a0, uint32_t a1, uint32_t a2, uint32_t a3, uint32_t db) {
  asm volatile("{\n.reg .b64 b;\nmov.b64 b, {%20, 0x8};\n"
      "wgmma.mma_async.sync.aligned.m64n32k16.f32.bf16.bf16 {"
      "%0,%1,%2,%3,%4,%5,%6,%7,%8,%9,%10,%11,%12,%13,%14,%15}, {%16,%17,%18,%19}, b, 0, 1, 1, 0;\n}"
      : "=f"(d[0]),"=f"(d[1]),"=f"(d[2]),"=f"(d[3]),"=f"(d[4]),"=f"(d[5]),"=f"(d[6]),"=f"(d[7]),"=f"(d[8]),"=f"(d[9]),"=f"(d[10]),"=f"(d[11]),"=f"(d[12]),
      "=f"(d[13]),"=f"(d[14]),"=f"(d[15])
      : "r"(a0), "r"(a1), "r"(a2), "r"(a3), "r"(db));
}
__device__ __forceinline__ void wg_rs96_u(float* d, uint32_t a0, uint32_t a1, uint32_t a2, uint32_t a3, uint32_t db) {
  asm volatile("{\n.reg .b64 b;\nmov.b64 b, {%52, 0xC0000010};\n"
      "wgmma.mma_async.sync.aligned.m64n96k16.f32.bf16.bf16 {"
      "%0,%1,%2,%3,%4,%5,%6,%7,%8,%9,%10,%11,%12,%13,%14,%15,%16,%17,%18,%19,%20,%21,%22,%23,%24,%25,%26,%27,%28,%29,%30,%31,%32,%33,%34,%35,%36,%37,%38,%39,"
      "%40,%41,%42,%43,%44,%45,%46,%47}, {%48,%49,%50,%51}, b, 1, 1, 1, 0;\n}"
      : "+f"(d[0]),"+f"(d[1]),"+f"(d[2]),"+f"(d[3]),"+f"(d[4]),"+f"(d[5]),"+f"(d[6]),"+f"(d[7]),"+f"(d[8]),"+f"(d[9]),"+f"(d[10]),"+f"(d[11]),"+f"(d[12]),
      "+f"(d[13]),"+f"(d[14]),"+f"(d[15]),"+f"(d[16]),"+f"(d[17]),"+f"(d[18]),"+f"(d[19]),"+f"(d[20]),"+f"(d[21]),"+f"(d[22]),"+f"(d[23]),"+f"(d[24]),
      "+f"(d[25]),"+f"(d[26]),"+f"(d[27]),"+f"(d[28]),"+f"(d[29]),"+f"(d[30]),"+f"(d[31]),"+f"(d[32]),"+f"(d[33]),"+f"(d[34]),"+f"(d[35]),"+f"(d[36]),
      "+f"(d[37]),"+f"(d[38]),"+f"(d[39]),"+f"(d[40]),"+f"(d[41]),"+f"(d[42]),"+f"(d[43]),"+f"(d[44]),"+f"(d[45]),"+f"(d[46]),"+f"(d[47])
      : "r"(a0), "r"(a1), "r"(a2), "r"(a3), "r"(db));
}
__device__ __forceinline__ void wg_rs128_u(float* d, uint32_t a0, uint32_t a1, uint32_t a2, uint32_t a3, uint32_t db) {
  asm volatile("{\n.reg .b64 b;\nmov.b64 b, {%68, 0xC0000010};\n"
      "wgmma.mma_async.sync.aligned.m64n128k16.f32.bf16.bf16 {"
      "%0,%1,%2,%3,%4,%5,%6,%7,%8,%9,%10,%11,%12,%13,%14,%15,%16,%17,%18,%19,%20,%21,%22,%23,%24,%25,%26,%27,%28,%29,%30,%31,%32,%33,%34,%35,%36,%37,%38,%39,"
      "%40,%41,%42,%43,%44,%45,%46,%47,%48,%49,%50,%51,%52,%53,%54,%55,%56,%57,%58,%59,%60,%61,%62,%63}, {%64,%65,%66,%67}, b, 1, 1, 1, 0;\n}"
      : "+f"(d[0]),"+f"(d[1]),"+f"(d[2]),"+f"(d[3]),"+f"(d[4]),"+f"(d[5]),"+f"(d[6]),"+f"(d[7]),"+f"(d[8]),"+f"(d[9]),"+f"(d[10]),"+f"(d[11]),"+f"(d[12]),
      "+f"(d[13]),"+f"(d[14]),"+f"(d[15]),"+f"(d[16]),"+f"(d[17]),"+f"(d[18]),"+f"(d[19]),"+f"(d[20]),"+f"(d[21]),"+f"(d[22]),"+f"(d[23]),"+f"(d[24]),
      "+f"(d[25]),"+f"(d[26]),"+f"(d[27]),"+f"(d[28]),"+f"(d[29]),"+f"(d[30]),"+f"(d[31]),"+f"(d[32]),"+f"(d[33]),"+f"(d[34]),"+f"(d[35]),"+f"(d[36]),
      "+f"(d[37]),"+f"(d[38]),"+f"(d[39]),"+f"(d[40]),"+f"(d[41]),"+f"(d[42]),"+f"(d[43]),"+f"(d[44]),"+f"(d[45]),"+f"(d[46]),"+f"(d[47]),"+f"(d[48]),
      "+f"(d[49]),"+f"(d[50]),"+f"(d[51]),"+f"(d[52]),"+f"(d[53]),"+f"(d[54]),"+f"(d[55]),"+f"(d[56]),"+f"(d[57]),"+f"(d[58]),"+f"(d[59]),"+f"(d[60]),
      "+f"(d[61]),"+f"(d[62]),"+f"(d[63])
      : "r"(a0), "r"(a1), "r"(a2), "r"(a3), "r"(db));
}
__device__ __forceinline__ void wg_fence() { asm volatile("wgmma.fence.sync.aligned;" ::: "memory"); }
__device__ __forceinline__ void wg_commit() { asm volatile("wgmma.commit_group.sync.aligned;" ::: "memory"); }
template <int N> __device__ __forceinline__ void wg_wait() { asm volatile("wgmma.wait_group.sync.aligned %0;" ::"n"(N) : "memory"); }
template <int N> __device__ __forceinline__ void pin(float* d) {
#pragma unroll
  for (int i = 0; i < N; i++) asm volatile("" : "+f"(d[i])::"memory");
}
__device__ __forceinline__ uint32_t mkdesc(uint32_t addr, uint32_t lbo) { return ((addr & 0x3FFFF) >> 4) | ((lbo >> 4) << 16); }
__device__ __forceinline__ void proxy_fence() { asm volatile("fence.proxy.async.shared::cta;" ::: "memory"); }
__device__ __forceinline__ void proxy_fence_global() { asm volatile("fence.proxy.async.global;" ::: "memory"); }
__device__ __forceinline__ void mbar_init(uint32_t b, int c) { asm volatile("mbarrier.init.shared::cta.b64 [%0], %1;" ::"r"(b), "r"(c) : "memory"); }
__device__ __forceinline__ void mbar_arrive(uint32_t b) { asm volatile("mbarrier.arrive.shared::cta.b64 _, [%0];" ::"r"(b) : "memory"); }
__device__ __forceinline__ void mbar_wait(uint32_t b, int ph) {
  asm volatile("{\n.reg .pred p, q;\n.reg .u32 c;\nmbarrier.try_wait.parity.shared::cta.b64 p, [%0], %1;\n@p bra DONE;\nmov.u32 c, 0;\n"
               "LOOP:\nmbarrier.try_wait.parity.shared::cta.b64 p, [%0], %1;\nadd.u32 c, c, 1;\nsetp.lt.and.u32 q, c, %2, !p;\n@q bra LOOP;\nDONE:\n}"
               ::"r"(b), "r"(ph), "n"(SPIN_LIMIT) : "memory");
}
#define BAR_SYNC(id, n) asm volatile("bar.sync %0, %1;" ::"r"(id), "n"(n) : "memory")
#define BAR_ARRIVE(id, n) asm volatile("bar.arrive %0, %1;" ::"r"(id), "n"(n) : "memory")

__device__ __forceinline__ uint32_t pack2(float lo, float hi) {
  uint32_t r;
  asm("cvt.rn.bf16x2.f32 %0, %1, %2;" : "=r"(r) : "f"(hi), "f"(lo));
  return r;
}
__device__ __forceinline__ uint32_t cpy(uint32_t v) { uint32_t r; asm volatile("mov.b32 %0, %1;" : "=r"(r) : "r"(v)); return r; }
__device__ __forceinline__ uint32_t tagchk(uint32_t a, uint32_t b, uint32_t par) {
  uint32_t r;
  asm("lop3.b32 %0, %1, %2, %3, 0x7E;" : "=r"(r) : "r"(a), "r"(b), "r"(par));
  return r;
}
__device__ __forceinline__ uint32_t pack_tag(float lo, float hi, uint32_t par) {
  const uint32_t t = (__float_as_uint(lo) + ((par ^ 1u) << 16)) >> 16;
  return __byte_perm(pack2(0.f, hi), (t & ~1u) | par, 0x3254);
}
__device__ __forceinline__ bool tagbad(uint32_t v) { return cpy(v) & 1u; }
__device__ __forceinline__ float lo16(uint32_t w) { return __uint_as_float(w << 16); }
__device__ __forceinline__ float hi16(uint32_t w) { return __uint_as_float(w & 0xffff0000u); }
__device__ __forceinline__ float bfr(float v) { return lo16(pack2(v, 0.f)); }
__device__ __forceinline__ float tanh_fast(float v) { float r; asm("tanh.approx.f32 %0, %1;" : "=f"(r) : "f"(v)); return r; }
__device__ __forceinline__ void sts32(uint32_t a, uint32_t v) { asm volatile("st.shared.u32 [%0], %1;" ::"r"(a), "r"(v) : "memory"); }
__device__ __forceinline__ void sts16(uint32_t a, uint32_t v) { asm volatile("st.shared.u16 [%0], %1;" ::"r"(a), "h"((uint16_t)v) : "memory"); }
__device__ __forceinline__ void sts64(uint32_t a, uint32_t x, uint32_t y) { asm volatile("st.shared.v2.u32 [%0], {%1,%2};" ::"r"(a), "r"(x), "r"(y) : "memory"); }
__device__ __forceinline__ void sts128(uint32_t a, uint32_t x, uint32_t y, uint32_t z, uint32_t w) {
  asm volatile("st.shared.v4.u32 [%0], {%1,%2,%3,%4};" ::"r"(a), "r"(x), "r"(y), "r"(z), "r"(w) : "memory");
}
__device__ __forceinline__ uint32_t lds32(uint32_t a) { uint32_t v; asm volatile("ld.shared.u32 %0, [%1];" : "=r"(v) : "r"(a) : "memory"); return v; }
__device__ __forceinline__ float ldsf(uint32_t a) { return __uint_as_float(lds32(a)); }
__device__ __forceinline__ uint2 lds64(uint32_t a) { uint2 v; asm volatile("ld.shared.v2.u32 {%0,%1}, [%2];" : "=r"(v.x), "=r"(v.y) : "r"(a) : "memory"); return v; }
__device__ __forceinline__ uint4 lds128(uint32_t a) {
  uint4 v; asm volatile("ld.shared.v4.u32 {%0,%1,%2,%3}, [%4];" : "=r"(v.x), "=r"(v.y), "=r"(v.z), "=r"(v.w) : "r"(a) : "memory"); return v;
}
__device__ __forceinline__ float4 lds128f(uint32_t a) {
  float4 v; asm volatile("ld.shared.v4.f32 {%0,%1,%2,%3}, [%4];" : "=f"(v.x), "=f"(v.y), "=f"(v.z), "=f"(v.w) : "r"(a) : "memory"); return v;
}
__device__ __forceinline__ uint4 ldg_strong128(const void* p) {
  uint4 v;
  asm volatile("{\n.reg .b64 a,b;\nld.relaxed.gpu.global.v2.b64 {a,b}, [%4];\nmov.b64 {%0,%1}, a;\nmov.b64 {%2,%3}, b;\n}"
               : "=r"(v.x), "=r"(v.y), "=r"(v.z), "=r"(v.w) : "l"(p) : "memory");
  return v;
}
__device__ __forceinline__ void stg_strong128(void* p, uint32_t x, uint32_t y, uint32_t z, uint32_t w) {
  asm volatile("{\n.reg .b64 a,b;\nmov.b64 a, {%1,%2};\nmov.b64 b, {%3,%4};\nst.relaxed.gpu.global.v2.b64 [%0], {a,b};\n}"
               ::"l"(p), "r"(x), "r"(y), "r"(z), "r"(w) : "memory");
}
__device__ __forceinline__ void stg_strong64(void* p, uint32_t x, uint32_t y) {
  asm volatile("{\n.reg .b64 a;\nmov.b64 a, {%1,%2};\nst.relaxed.gpu.global.b64 [%0], a;\n}" ::"l"(p), "r"(x), "r"(y) : "memory");
}
__device__ __forceinline__ void stg_hint(void* p, uint32_t v, int lane) {
  asm volatile("{\n.reg .pred p;\nsetp.eq.u32 p, %2, 0;\n@p st.relaxed.gpu.global.u32 [%0], %1;\n}" ::"l"(p), "r"(v), "r"(lane) : "memory");
}
__device__ __forceinline__ void flag_wait(const unsigned int* flag, uint32_t target) {
#pragma unroll 1
  for (int it = 0; it < POLL_LIMIT; it++) {
    uint32_t v;
    asm volatile("ld.acquire.gpu.global.u32 %0, [%1];" : "=r"(v) : "l"(flag) : "memory");
    if ((int)(v - target) >= 0) return;
  }
}

__device__ __forceinline__ float2 cmul(float2 a, float2 b) { return make_float2(fmaf(a.x, b.x, -a.y * b.y), fmaf(a.x, b.y, a.y * b.x)); }
__device__ __forceinline__ float2 csq(float2 a) { return make_float2(fmaf(a.x, a.x, -a.y * a.y), (a.x + a.x) * a.y); }
__device__ __forceinline__ uint32_t packh(float lo, float hi) {
  uint32_t r;
  asm("cvt.rn.f16x2.f32 %0, %1, %2;" : "=r"(r) : "f"(hi), "f"(lo));
  return r;
}
__device__ __forceinline__ uint2 hpair(float2 a, float2 b) { return make_uint2(packh(a.x, b.x), packh(a.y, b.y)); }
__device__ __forceinline__ uint2 hcmul(uint2 a, uint32_t m) {
  uint2 r;
  asm("{\n.reg .b16 l,h;\n.reg .b32 c,d,p,q,n;\nmov.b32 {l,h}, %4;\nmov.b32 c, {l,l};\nmov.b32 d, {h,h};\n"
      "mul.rn.f16x2 p, %2, c;\nmul.rn.f16x2 q, %2, d;\nneg.f16x2 n, %3;\n"
      "fma.rn.f16x2 %0, n, d, p;\nfma.rn.f16x2 %1, %3, c, q;\n}" : "=r"(r.x), "=r"(r.y) : "r"(a.x), "r"(a.y), "r"(m));
  return r;
}
__device__ __forceinline__ uint32_t hmulp(float2 z) { return packh(z.x, z.y); }
__device__ __forceinline__ float2 cexp2t(float l2, float turns) {
  float mag, s, c;
  asm("ex2.approx.ftz.f32 %0, %1;" : "=f"(mag) : "f"(l2));
  float k = __fadd_rn(__fadd_rn(turns, 12582912.f), -12582912.f);
  float r = (turns - k) * 6.283185307179586f;
  asm("sin.approx.ftz.f32 %0, %1;" : "=f"(s) : "f"(r));
  asm("cos.approx.ftz.f32 %0, %1;" : "=f"(c) : "f"(r));
  return make_float2(mag * c, mag * s);
}

__device__ __forceinline__ bool elect() {
  uint32_t p;
  asm volatile("{\n.reg .pred P;\nelect.sync _|P, 0xffffffff;\nselp.u32 %0,1,0,P;\n}" : "=r"(p));
  return p;
}
__device__ __forceinline__ void expect_tx(uint32_t bar, uint32_t bytes) {
  asm volatile("mbarrier.arrive.expect_tx.shared::cta.b64 _, [%0], %1;" ::"r"(bar), "r"(bytes) : "memory");
}
__device__ __forceinline__ void tma2d(uint32_t dst, const CUtensorMap* m, uint32_t bar, int c0, int c1) {
  asm volatile("cp.async.bulk.tensor.2d.shared::cluster.global.mbarrier::complete_tx::bytes [%0], [%1, {%3,%4}], [%2];"
               ::"r"(dst), "l"(m), "r"(bar), "r"(c0), "r"(c1) : "memory");
}
__device__ __forceinline__ void tma3d(uint32_t dst, const CUtensorMap* m, uint32_t bar, int c0, int c1, int c2) {
  asm volatile("cp.async.bulk.tensor.3d.shared::cluster.global.mbarrier::complete_tx::bytes [%0], [%1, {%3,%4,%5}], [%2];"
               ::"r"(dst), "l"(m), "r"(bar), "r"(c0), "r"(c1), "r"(c2) : "memory");
}
__device__ __forceinline__ void bulk_load(uint32_t dst, const void* src, uint32_t bytes, uint32_t bar) {
  asm volatile("cp.async.bulk.shared::cluster.global.mbarrier::complete_tx::bytes [%0], [%1], %2, [%3];"
               ::"r"(dst), "l"(src), "r"(bytes), "r"(bar) : "memory");
}
__device__ __forceinline__ void spin(uint32_t cycles) {
  const uint32_t c0 = clock();
  while ((uint32_t)clock() - c0 < cycles) {}
}
__device__ __forceinline__ int fresh_tw() { int v; asm volatile("mov.u32 %0, %%tid.x;" : "=r"(v)); return v & 127; }

__device__ __forceinline__ float shx(float v, int o) { return __shfl_xor_sync(0xffffffffu, v, o); }
__device__ __forceinline__ float ln_rden(float var) {
  float s, r;
  asm("sqrt.approx.f32 %0, %1;" : "=f"(s) : "f"(bfr(bfr(var) + 1e-5f)));
  asm("rcp.approx.f32 %0, %1;" : "=f"(r) : "f"(bfr(s)));
  return r;
}
__device__ __forceinline__ uint32_t hadd2(uint32_t a, uint32_t b) {
  uint32_t r;
  asm("add.rn.bf16x2 %0, %1, %2;" : "=r"(r) : "r"(a), "r"(b));
  return r;
}
__device__ __forceinline__ uint32_t hmul2(uint32_t a, uint32_t b) {
  uint32_t r;
  asm("mul.rn.bf16x2 %0, %1, %2;" : "=r"(r) : "r"(a), "r"(b));
  return r;
}
__device__ __forceinline__ uint32_t hsub2(uint32_t a, uint32_t b) {
  uint32_t r;
  asm("sub.rn.bf16x2 %0, %1, %2;" : "=r"(r) : "r"(a), "r"(b));
  return r;
}
__device__ __forceinline__ uint32_t get_parity(uint32_t sb) {
  mbar_wait(sb + BAR_OFF + 8 * B_EPOCH, 0);
  return cpy(((lds32(sb + CNT_OFF) >> 8) + 1u) & 1u);
}
__device__ __forceinline__ void ln_rows(uint4* g_ab, const uint32_t* xa, const uint32_t* xb, int unit, uint32_t tbuf, int rp, int lane) {
  const float pa = lo16(__shfl_sync(0xffffffffu, xa[0], 0)), pb = lo16(__shfl_sync(0xffffffffu, xb[0], 0));
  float s1a = 0.f, s2a = 0.f, s1b = 0.f, s2b = 0.f;
#pragma unroll
  for (int q = 0; q < 7; q++) {
    const float a0 = lo16(xa[q]) - pa, a1 = hi16(xa[q]) - pa, b0 = lo16(xb[q]) - pb, b1 = hi16(xb[q]) - pb;
    s1a += a0 + a1; s1b += b0 + b1;
    s2a = fmaf(a0, a0, fmaf(a1, a1, s2a)); s2b = fmaf(b0, b0, fmaf(b1, b1, s2b));
  }
  const bool up = lane & 16, sq = lane & 8;
  float s1 = (up ? s1b : s1a) + shx(up ? s1a : s1b, 16), s2 = (up ? s2b : s2a) + shx(up ? s2a : s2b, 16);
  float s = (sq ? s2 : s1) + shx(sq ? s1 : s2, 8);
  s += shx(s, 4); s += shx(s, 2); s += shx(s, 1);
  const float o = shx(s, 8);
  const float md = (sq ? o : s) * (1.f / DM), var = fmaxf(fmaf(-md, md, (sq ? s : o) * (1.f / DM)), 0.f);
  const float mean = (up ? pb : pa) + md;
  const uint32_t m2x = pack2(mean, mean);
  const float m1 = lo16(m2x), r1 = ln_rden(var), r2 = ln_rden(var * r1 * r1);
  if ((lane & 15) == 0) {
    const float a = r1 * r2, al = __fdividef(1.f, a), be = -fmaf(bfr((mean - m1) * r1), __fdividef(1.f, r1), m1);
    const float beh = bfr(be), alh = bfr(al);
    g_ab[unit * 16 + rp * 2 + (lane >> 4)] = make_uint4(pack2(be - beh, beh), pack2(beh, alh), pack2(al - alh, 0.f),
                                                        __float_as_uint(a) & ~0x80u);
  }
  const uint32_t mo = __shfl_xor_sync(0xffffffffu, m2x, 16);
  const float ro = shx(r1, 16);
  const uint32_t ma = up ? mo : m2x, mb = up ? m2x : mo;
  const float ra = up ? ro : r1, rb = up ? r1 : ro;
  const uint32_t tb = tbuf + (18 * lane + rp) * 4;
#pragma unroll
  for (int q = 0; q < 7; q++) {
    const uint32_t da = hsub2(xa[q], ma), db = hsub2(xb[q], mb);
    sts32(tb + q * 2304, pack2(lo16(da) * ra, lo16(db) * rb));
    sts32(tb + q * 2304 + 36, pack2(hi16(da) * ra, hi16(db) * rb));
  }
}
__device__ __forceinline__ void ln_load(const __nv_bfloat16* x, int unit, int warp, int lane, uint32_t* xr) {
  const uint32_t* p = reinterpret_cast<const uint32_t*>(x + (size_t)(unit * 16 + warp * 2) * DM) + lane;
#pragma unroll
  for (int q = 0; q < 14; q++) asm volatile("ld.global.nc.u32 %0, [%1];" : "=r"(xr[q]) : "l"(p + q * 32));
}
__device__ __forceinline__ void ln_store(uint4* g_xT, int unit, uint32_t tbuf, int tid) {
  const uint32_t a = tbuf + (tid >> 1) * 36 + (tid & 1) * 16;
  uint4* dst = g_xT + (tid >> 1) * 276 + (127 - unit) * 2 + ((tid ^ ((127 - unit) >> 2)) & 1);
  uint4 v[4];
#pragma unroll
  for (int r = 0; r < 4; r++)
    if (r < 3 || tid < 128) v[r] = make_uint4(lds32(a + r * 4608), lds32(a + r * 4608 + 4), lds32(a + r * 4608 + 8), lds32(a + r * 4608 + 12));
#pragma unroll
  for (int r = 0; r < 4; r++)
    if (r < 3 || tid < 128) dst[r * 128 * 276] = v[r];
}
__device__ __forceinline__ void add8(float* s, uint4 v) {
  s[0] += lo16(v.x); s[1] += hi16(v.x); s[2] += lo16(v.y); s[3] += hi16(v.y);
  s[4] += lo16(v.z); s[5] += hi16(v.z); s[6] += lo16(v.w); s[7] += hi16(v.w);
}
__device__ __forceinline__ uint32_t vkey(int blk) { return ((blk & 2) << 4) | ((blk & 4) << 2); }

__global__ void __launch_bounds__(512, 1)
s4_mixer_kernel(const __grid_constant__ Params P, const __grid_constant__ CUtensorMap mx, const __grid_constant__ CUtensorMap mw1,
                const __grid_constant__ CUtensorMap mw2, const __grid_constant__ CUtensorMap mo) {
  extern __shared__ __align__(1024) uint8_t smem_raw[];
  const uint32_t sb = (uint32_t)__cvta_generic_to_shared(smem_raw);
  const int tid = threadIdx.x, lane = tid & 31;
  const int warp = __shfl_sync(0xffffffffu, tid >> 5, 0), wg = warp >> 2;
  const int cta = blockIdx.x, nconv = gridDim.x - NMLP;
  const bool is_mlp = cta < NMLP;
  const int tile = cta & 15, sl = cta >> 4;
  const uint32_t tbuf = sb + (is_mlp ? 9 * SLOT : 0), bars = sb + BAR_OFF;

  if (is_mlp && wg != 2) spin(DELAY0);
  const int w0 = wg * nconv + cta - NMLP;
  if (wg == 3) {
    asm volatile("setmaxnreg.dec.sync.aligned.u32 32;");
    if (warp == 12) {
      if (elect()) {
        asm volatile("prefetch.tensormap [%0];" ::"l"(&mx) : "memory");
        asm volatile("prefetch.tensormap [%0];" ::"l"(&mw1) : "memory");
#pragma unroll
        for (int i = 0; i < NBAR; i++) mbar_init(bars + 8 * i, i < B_CONST ? 1 : (i == B_CONST ? 3 : 8));
        asm volatile("fence.mbarrier_init.release.cluster;" ::: "memory");
        if (is_mlp) {
          expect_tx(bars, 3 * SLOT);
          tma3d(sb + SLOT, &mw1, bars, 0, 0, sl * 4);
          tma2d(sb, &mx, bars, 0, tile * 128);
        }
      }
      __syncwarp();
      BAR_ARRIVE(9, 160);
      BAR_ARRIVE(10, 160);
      BAR_ARRIVE(11, 160);
      BAR_ARRIVE(7, 128);
#pragma unroll 1
      for (int j = 1; j < 6 && !is_mlp; j++) {
        if (elect()) {
          const int w = j < 3 ? 2 - j : 5 - j;
          const uint32_t dst = sb + (j < 3 ? w * CA_BYTES + STG_BYTES : 2 * CA_BYTES + 4 * U_BYTES + w * 6144), bar = bars + 8 * (w + (j < 3 ? 0 : 3));
          const int o = (NMLP + (j < 3 ? 0 : NEXP) + min(w * nconv + cta - NMLP, NEXP - 1)) * 512;
          expect_tx(bar, 6144);
#pragma unroll
          for (int i = 0; i < 6; i++) bulk_load(dst + i * 1024, (&P.Are)[i] + o, 1024, bar);
        }
      }
      if (is_mlp) {
        int st = 1;
#pragma unroll 1
        for (int kc = 1; kc < 7; kc++) {
          if (kc >= 3) mbar_wait(bars + 8 * (B_E1 - 3 + kc), 0); else spin(START_GAP);
          __syncwarp();
          if (elect()) {
            const uint32_t bar = bars + 8 * (B_F1 + kc), dst = sb + st * (3 * SLOT);
            expect_tx(bar, 3 * SLOT);
            tma3d(dst + SLOT, &mw1, bar, 0, kc * 64, sl * 4);
            tma2d(dst, &mx, bar, kc * 64, tile * 128);
            if (kc == 3) {
              asm volatile("cp.async.bulk.prefetch.L2.global [%0], %1;" ::"l"(P.w2 + (size_t)cta * 16 * DM), "r"(16 * DM * 2) : "memory");
              asm volatile("prefetch.tensormap [%0];" ::"l"(&mw2) : "memory");
              asm volatile("prefetch.tensormap [%0];" ::"l"(&mo) : "memory");
            }
          }
          st = st == 2 ? 0 : st + 1;
        }
        int c = sl;
        st = 4;
#pragma unroll 1
        for (int k = 0; k < 8; k++) {
          mbar_wait(bars + 8 * (B_E1 + (k < 3 ? 4 + k : (k < 7 ? 3 + k : 11))), 0);
          __syncwarp();
          c = c == 6 ? 0 : c + 1;
          if (elect()) {
            if (k < 7) {
              expect_tx(bars + 8 * (B_F2 + k), 2 * SLOT);
              tma2d(sb + st * SLOT, &mw2, bars + 8 * (B_F2 + k), c * 64, sl * 256);
            } else {
              expect_tx(bars + 8 * B_X, SLOT);
              tma2d(sb + 5 * SLOT, &mx, bars + 8 * B_X, sl * 64, tile * 128);
            }
          }
          st = (st + 2) & 7;
        }
      }
    } else {
      uint32_t par, cnt0 = 0;
      if (tid == 416) asm volatile("ld.relaxed.gpu.global.u32 %0, [%1];" : "=r"(cnt0) : "l"(P.scr->flag) : "memory");
      BAR_SYNC(7, 128);
      if (tid == 416) { sts32(sb + CNT_OFF, cnt0); mbar_arrive(bars + 8 * B_EPOCH); }
      __syncwarp();
      par = get_parity(sb);
      if (warp == 13) {
        BAR_SYNC(5, 288);
        TSX(5);
        if (lane == 0) {
          asm volatile("fence.acq_rel.gpu;" ::: "memory");
          TSX(6);
          asm volatile("red.relaxed.gpu.global.add.u32 [%0], %1;" ::"l"(P.scr->flag), "r"(blockIdx.x == 0 ? 257u - gridDim.x : 1u) : "memory");
          flag_wait(P.scr->flag, (cnt0 & ~255u) + 256u);
          TSX(17);
        }
        __syncwarp();
#pragma unroll 1
        for (int w = 2; w >= (is_mlp ? 2 : 0); w--) {
          if (elect()) {
            const uint4* src = P.scr->xT + (is_mlp ? cta : NMLP + NEXP + min(w * nconv + cta - NMLP, NEXP - 1)) * 552;
            const uint32_t dst = sb + (w == 2 ? UP_OFF : 2 * CA_BYTES + w * 2 * U_BYTES);
            if (w == 2) { proxy_fence_global(); expect_tx(bars + 8 * B_U, (is_mlp ? 2 : 6) * U_COPY); }
            bulk_load(dst, src, U_COPY, bars + 8 * B_U);
            bulk_load(dst + U_BYTES, src + 276, U_COPY, bars + 8 * B_U);
          }
        }
        if (!is_mlp) return;
        uint4 v[4];
#pragma unroll
        for (int i = 0; i < 4; i++) v[i] = __ldcg(P.scr->ab + tile * 128 + i * 32 + lane);
#pragma unroll
        for (int i = 0; i < 11; i++) sts128(sb + BX_OFF + (lane >> 3) * 2048 + 640 + i * 128 + (lane & 7) * 16, 0u, 0u, 0u, 0u);
#pragma unroll
        for (int i = 0; i < 4; i++) sts128(sb + AX_OFF + (i * 32 + lane) * 16, v[i].x, v[i].y, v[i].z, v[i].w);
      } else {
        if (!is_mlp) return;
        {
          const int rq = cta / 28, cg = cta - rq * 28, rg = rq * 2 + (warp & 1);
          const uint32_t* wp = reinterpret_cast<const uint32_t*>(P.w1 + (size_t)rg * 56 * FF + cg * 64) + lane;
          float c0 = 0.f, c1 = 0.f;
#pragma unroll 1
          for (int r = 0; r < 3; r++) {
            uint32_t w[19];
#pragma unroll
            for (int i = 0; i < 19; i++) w[i] = (i < 18 || r < 2) ? __ldg(wp + i * (FF / 2)) : 0u;
#pragma unroll
            for (int i = 0; i < 19; i++) { c0 += lo16(w[i]); c1 += hi16(w[i]); }
            wp += 19 * (FF / 2);
          }
          if (warp == 15) {
            mbar_wait(bars + 8 * B_E1, 0);
            sts64(sb + BX_OFF + 12288 + lane * 8, __float_as_uint(c0), __float_as_uint(c1));
            BAR_ARRIVE(8, 64);
          } else {
            BAR_SYNC(8, 64);
            const uint2 o = lds64(sb + BX_OFF + 12288 + lane * 8);
            stg_strong64(P.scr->cs + rq * FF + cg * 64 + lane * 2, (__float_as_uint(c0 + __uint_as_float(o.x)) & ~1u) | par,
                         __float_as_uint(c1 + __uint_as_float(o.y)));
          }
        }
        TSX(38);
        const int col = (warp & 1) * 128 + lane * 4;
        const uint2 b1w = __ldg(reinterpret_cast<const uint2*>(P.b1 + sl * 256 + col));
        mbar_wait(bars + 8 * (B_E1 + CSW), 0);
        const float* cp = P.scr->cs + sl * 256 + col;
        uint4 v[4];
#pragma unroll 1
        for (int it = 0; it < POLL_LIMIT; it++) {
          uint32_t bad = 0;
#pragma unroll
          for (int i = 0; i < 4; i++) { v[i] = ldg_strong128(cp + i * FF); bad |= tagchk(v[i].x, v[i].z, par); }
          if (!tagbad(bad)) break;
          __nanosleep(100);
        }
        float c[4];
#pragma unroll
        for (int i = 0; i < 4; i++)
          c[i] = (__uint_as_float((&v[0].x)[i]) + __uint_as_float((&v[1].x)[i])) + (__uint_as_float((&v[2].x)[i]) + __uint_as_float((&v[3].x)[i]));
        TSX(39);
        const uint32_t h0 = pack2(c[0], c[1]), h1 = pack2(c[2], c[3]);
        const uint32_t l0 = pack2(c[0] - lo16(h0), c[1] - hi16(h0)), l1 = pack2(c[2] - lo16(h1), c[3] - hi16(h1));
        const uint32_t ba = sb + BX_OFF + (col >> 6) * 2048 + (lane & 1) * 8, ck = (lane >> 1) & 7;
        sts64(ba + (ck << 4), h0, h1);
        sts64(ba + 128 + ((ck ^ 1) << 4), h0, h1);
        sts64(ba + 256 + ((ck ^ 2) << 4), l0, l1);
        sts64(ba + 384 + ((ck ^ 3) << 4), b1w.x, b1w.y);
        sts64(ba + 512 + ((ck ^ 4) << 4), b1w.x, b1w.y);
      }
      proxy_fence();
      __syncwarp();
      if (lane == 0) mbar_arrive(bars + 8 * B_CONST);
#pragma unroll 1
      for (int b = warp == 14 ? 6 : (warp == 13 ? 0 : 1); b < (warp == 14 ? 7 : 6); b += 2) {
        const uint4* hp = b < 6 ? reinterpret_cast<const uint4*>(P.scr->hintp + (tile * 7 + sl) * 64 + b * 8) : reinterpret_cast<const uint4*>(P.scr->hints + sl * 256) + lane * 2;
#pragma unroll 1
        for (int it = 0; it < POLL_LIMIT; it++) {
          const uint4 e0 = ldg_strong128(hp), e1 = ldg_strong128(hp + 1);
          const uint32_t bad = tagchk(e0.x, e0.y, par) | tagchk(e0.z, e0.w, par) | tagchk(e1.x, e1.y, par) | tagchk(e1.z, e1.w, par);
          if (it == 0) mbar_wait(bars + 8 * (B_SENT + (b < 6 ? (b == 2 ? 3 : b) : 5)), 0);
          if (!__any_sync(0xffffffffu, tagbad(bad))) break;
        }
        spin(b < 4 ? HD0 : (b < 6 ? HD1 : HD2));
        __syncwarp();
        if (elect()) {
          const void* src = b < 6 ? (const void*)(P.scr->part + ((tile * 7 + sl) * 6 + b) * 1024) : (const void*)(P.scr->s + (tile * DM + sl * 64) * 32);
          expect_tx(bars + 8 * (B_PB + b), SLOT);
          bulk_load(sb + ((0x7643298u >> (4 * b)) & 15u) * SLOT, src, SLOT, bars + 8 * (B_PB + b));
        }
        TSX(10 + b);
      }
    }
  } else if (is_mlp && wg < 2) {
    const int g = lane >> 2, t = lane & 3;
    uint32_t xr[14];
    ln_load(P.x, cta, warp, lane, xr);
    asm volatile("setmaxnreg.inc.sync.aligned.u32 176;");
    uint32_t h[64];
    float ra0, ra1;
    {
      float acc[128];
#pragma unroll
      for (int i = 0; i < 128; i++) acc[i] = 0.f;
      pin<128>(acc);
      BAR_SYNC(9 + wg, 160);
      ln_rows(P.scr->ab, xr, xr + 7, cta, tbuf, warp, lane);
      TS(18);
      if (wg == 0) BAR_ARRIVE(4, 256);
      else {
        BAR_SYNC(4, 256);
        ln_store(P.scr->xT, cta, tbuf, tid - 128);
        ln_store(P.scr->xT, cta, tbuf, tid);
      }
      BAR_ARRIVE(5, 288);
      TS(1);
      const uint32_t arow = (warp * 16 + (lane & 15)) * 128, asw = ((lane >> 4) ^ (lane & 7)) << 4;
      int st = 0;
#pragma unroll 1
      for (int kc = 0; kc < 7; kc++) {
        const uint32_t sa = sb + st * (3 * SLOT), db = mkdesc(sa + SLOT, 8192);
        st = st == 2 ? 0 : st + 1;
        mbar_wait(bars + 8 * (B_F1 + kc), 0);
        __syncwarp();
        TS(24 + kc);
        uint32_t a[4][4];
#pragma unroll
        for (int ks = 0; ks < 4; ks++)
          asm volatile("ldmatrix.sync.aligned.m8n8.x4.shared.b16 {%0,%1,%2,%3}, [%4];"
                       : "=r"(a[ks][0]), "=r"(a[ks][1]), "=r"(a[ks][2]), "=r"(a[ks][3]) : "r"(sa + arow + (asw ^ (ks * 32))) : "memory");
        wg_fence();
#pragma unroll
        for (int ks = 0; ks < 4; ks++) {
          wg_rs128_t(acc, a[ks][0], a[ks][1], a[ks][2], a[ks][3], db + ks * 128);
          wg_rs128_t(acc + 64, a[ks][0], a[ks][1], a[ks][2], a[ks][3], db + 1024 + ks * 128);
        }
        wg_commit();
        wg_wait<0>();
        if (lane == 0) mbar_arrive(bars + 8 * (B_E1 + kc));
      }
      TS(3);
      mbar_wait(bars + 8 * B_CONST, 0);
      __syncwarp();
      TS(2);
      {
        uint32_t e[4];
        asm volatile("ldmatrix.sync.aligned.m8n8.x4.shared.b16 {%0,%1,%2,%3}, [%4];"
                     : "=r"(e[0]), "=r"(e[1]), "=r"(e[2]), "=r"(e[3]) : "r"(lane < 16 ? sb + AX_OFF + (warp * 16 + lane) * 16 : sb + BX_OFF + 1024) : "memory");
        ra0 = __uint_as_float(__shfl_sync(0xffffffffu, e[0], lane | 3));
        ra1 = __uint_as_float(__shfl_sync(0xffffffffu, e[1], lane | 3));
        const uint32_t db = mkdesc(sb + BX_OFF, 2048);
        wg_fence();
        wg_rs128_t(acc, e[0], e[1], e[2], e[3], db);
        wg_rs128_t(acc + 64, e[0], e[1], e[2], e[3], db + 256);
        wg_commit();
        wg_wait<0>();
        pin<128>(acc);
      }
      const float p0 = 0.7978845608028654f * ra0, q0 = 0.035677408136300125f * ra0 * ra0 * ra0;
      const float p1 = 0.7978845608028654f * ra1, q1 = 0.035677408136300125f * ra1 * ra1 * ra1;
#pragma unroll
      for (int j = 0; j < 64; j++) {
        const float w0 = acc[2 * j], w1 = acc[2 * j + 1], pp = (j & 1) ? p1 : p0, qq = (j & 1) ? q1 : q0;
        h[j] = pack2(fmaf(w0, tanh_fast(w0 * fmaf(w0 * w0, qq, pp)), w0), fmaf(w1, tanh_fast(w1 * fmaf(w1 * w1, qq, pp)), w1));
      }
    }
    TS(4);
    const uint32_t par = get_parity(sb);
    float acc[32];
    uint32_t b2w[8];
#pragma unroll
    for (int j = 0; j < 8; j++) b2w[j] = __ldg(reinterpret_cast<const uint32_t*>(P.b2 + sl * 64) + t + j * 4);
    if (wg == 1) spin(STAGGER);
    const uint32_t bo = warp * 128 + lane;
    {
      int c = sl, st = 4;
      mbar_wait(bars + 8 * B_F2, 0);
#pragma unroll 1
      for (int k = 0;; k++) {
        const uint32_t d0 = mkdesc(sb + st * SLOT, 8192);
        st = (st + 2) & 7;
        __syncwarp();
        wg_fence();
        wg_rs64_t_init(acc, h[0], h[1], h[2], h[3], d0);
#pragma unroll
        for (int s = 1; s < 16; s++) wg_rs64_t(acc, h[4 * s], h[4 * s + 1], h[4 * s + 2], h[4 * s + 3], d0 + s * 128);
        wg_commit();
        c = c == 6 ? 0 : c + 1;
        if (k < 6) mbar_wait(bars + 8 * (B_F2 + k + 1), 0);
        __syncwarp();
        wg_wait<0>();
        pin<32>(acc);
        TS(40 + k);
        if (k == 6) break;
        if (lane == 0) mbar_arrive(bars + 8 * (B_SENT + k));
        uint32_t pk[16];
#pragma unroll
        for (int i = 0; i < 16; i++) pk[i] = (i & 1) ? pack2(acc[2 * i], acc[2 * i + 1]) : ((pack2(acc[2 * i], acc[2 * i + 1]) & ~1u) | par);
        uint4* dst = P.scr->part + ((tile * 7 + c) * 6 + k) * 1024 + bo;
        asm volatile("{\n.reg .b64 a<8>;\nmov.b64 a0, {%1,%2};\nmov.b64 a1, {%3,%4};\nmov.b64 a2, {%5,%6};\nmov.b64 a3, {%7,%8};\n"
                     "mov.b64 a4, {%9,%10};\nmov.b64 a5, {%11,%12};\nmov.b64 a6, {%13,%14};\nmov.b64 a7, {%15,%16};\n"
                     "st.relaxed.gpu.global.v2.b64 [%0], {a0,a1};\nst.relaxed.gpu.global.v2.b64 [%0+512], {a2,a3};\n"
                     "st.relaxed.gpu.global.v2.b64 [%0+1024], {a4,a5};\nst.relaxed.gpu.global.v2.b64 [%0+1536], {a6,a7};\n}"
                     ::"l"(dst), "r"(pk[0]), "r"(pk[1]), "r"(pk[2]), "r"(pk[3]), "r"(pk[4]), "r"(pk[5]), "r"(pk[6]), "r"(pk[7]), "r"(pk[8]),
                     "r"(pk[9]), "r"(pk[10]), "r"(pk[11]), "r"(pk[12]), "r"(pk[13]), "r"(pk[14]), "r"(pk[15]) : "memory");
        stg_hint(P.scr->hintp + (tile * 7 + c) * 64 + k * 8 + warp, par, lane);
      }
    }
    const uint4* psrc = P.scr->part + (tile * 7 + sl) * 6 * 1024 + bo;
    auto refetch = [&](uint4* v, int b) {
#pragma unroll 1
      for (int it = 0; it < POLL_LIMIT; it++) {
        uint32_t bad = 0;
#pragma unroll
        for (int q = 0; q < 4; q++) { v[q] = ldg_strong128(psrc + b * 1024 + q * 32); bad |= tagchk(v[q].x, v[q].z, par); }
        if (!tagbad(bad)) break;
      }
    };
    uint32_t xv[16], sv[16];
    const uint32_t xrow = sb + 5 * SLOT + (warp * 16 + (lane & 15)) * 128, xsw = ((lane >> 4) ^ (lane & 7)) << 4;
    auto hadd8 = [](uint4 a, uint4 b) { return make_uint4(hadd2(a.x, b.x), hadd2(a.y, b.y), hadd2(a.z, b.z), hadd2(a.w, b.w)); };
#pragma unroll
    for (int pr = 0; pr < 2; pr++) {
      mbar_wait(bars + 8 * (B_PB + 2 * pr), 0);
      mbar_wait(bars + 8 * (B_PB + 2 * pr + 1), 0);
      TS(32 + pr);
      uint4 v[2][4];
      uint32_t bad = 0;
#pragma unroll
      for (int q = 0; q < 8; q++) {
        v[q >> 2][q & 3] = lds128(sb + ((pr ? 2 : 8) + (q >> 2)) * SLOT + bo * 16 + (q & 3) * 512);
        bad |= tagchk(v[q >> 2][q & 3].x, v[q >> 2][q & 3].z, par);
      }
      if (__builtin_expect(tagbad(bad), 0)) { refetch(v[0], 2 * pr); refetch(v[1], 2 * pr + 1); }
#pragma unroll
      for (int q = 0; q < 4; q++) add8(acc + 8 * q, hadd8(v[0][q], v[1][q]));
    }
    mbar_wait(bars + 8 * B_X, 0);
    __syncwarp();
#pragma unroll
    for (int jj = 0; jj < 4; jj++)
      asm volatile("ldmatrix.sync.aligned.m8n8.x4.shared.b16 {%0,%1,%2,%3}, [%4];"
                   : "=r"(xv[4 * jj]), "=r"(xv[4 * jj + 1]), "=r"(xv[4 * jj + 2]), "=r"(xv[4 * jj + 3]) : "r"(xrow + (xsw ^ (jj * 32))) : "memory");
    ra0 *= 0.25f; ra1 *= 0.25f;
#pragma unroll
    for (int i = 0; i < 32; i++) {
      const uint32_t bh = hmul2(b2w[i >> 2], 0x3f003f00u);
      acc[i] = fmaf(acc[i], (i & 2) ? ra1 : ra0, (i & 1) ? hi16(bh) : lo16(bh));
    }
    TS(36);
    uint32_t gv[16];
    {
      mbar_wait(bars + 8 * (B_PB + 4), 0);
      mbar_wait(bars + 8 * (B_PB + 5), 0);
      TS(37);
      uint4 v[2][4];
      uint32_t bad = 0;
#pragma unroll
      for (int q = 0; q < 8; q++) { v[q >> 2][q & 3] = lds128(sb + (q < 4 ? 4 : 6) * SLOT + bo * 16 + (q & 3) * 512); bad |= tagchk(v[q >> 2][q & 3].x, v[q >> 2][q & 3].z, par); }
      if (__builtin_expect(tagbad(bad), 0)) { refetch(v[0], 4); refetch(v[1], 5); }
      __syncwarp();
#pragma unroll
      for (int i = 0; i < 16; i++) {
        const uint32_t w = hadd2((&v[0][i >> 2].x)[i & 3], (&v[1][i >> 2].x)[i & 3]);
        const float h0 = fmaf(lo16(w), (i & 1) ? ra1 : ra0, acc[2 * i]), h1 = fmaf(hi16(w), (i & 1) ? ra1 : ra0, acc[2 * i + 1]);
        gv[i] = pack2(fmaf(h0, tanh_fast(h0), h0), fmaf(h1, tanh_fast(h1), h1));
      }
    }
    TS(7);
    {
      mbar_wait(bars + 8 * B_S, 0);
      TS(9);
      const uint32_t so = (2 * t * 32 + ((((warp >> 1) * 8 + g) ^ (t * 4)) & 31)) * 2 + (warp & 1);
      uint32_t bad = 0;
#pragma unroll
      for (int j = 0; j < 16; j++) sv[j] = lds32(sb + 7 * SLOT + (so + (j >> 1) * 512 + (j & 1) * 64) * 4);
#pragma unroll
      for (int j = 0; j < 8; j++) bad |= tagchk(sv[2 * j], sv[2 * j + 1], par);
      if (__builtin_expect(tagbad(bad), 0)) {
#pragma unroll 1
        for (int it = 0; it < POLL_LIMIT; it++) {
          bad = 0;
#pragma unroll
          for (int j = 0; j < 16; j++) {
            asm volatile("ld.relaxed.gpu.global.u32 %0, [%1];" : "=r"(sv[j])
                         : "l"(reinterpret_cast<const uint32_t*>(P.scr->s + (tile * DM + sl * 64) * 32) + so + (j >> 1) * 512 + (j & 1) * 64) : "memory");
            bad |= sv[j] ^ par;
          }
          if (!tagbad(bad)) break;
        }
      }
      __syncwarp();
    }
#pragma unroll
    for (int jj = 0; jj < 4; jj++) {
      uint32_t ov[4];
#pragma unroll
      for (int i = 0; i < 4; i++) {
        const int e = 4 * jj + (i & 2);
        asm("fma.rn.bf16x2 %0, %1, %2, %3;" : "=r"(ov[i]) : "r"(__byte_perm(sv[e], sv[e + 1], (i & 1) ? 0x7632 : 0x5410)), "r"(gv[4 * jj + i]), "r"(xv[4 * jj + i]));
      }
      asm volatile("stmatrix.sync.aligned.m8n8.x4.shared.b16 [%0], {%1,%2,%3,%4};" ::"r"(xrow + (xsw ^ (jj * 32))), "r"(ov[0]), "r"(ov[1]), "r"(ov[2]), "r"(ov[3]) : "memory");
    }
    proxy_fence();
    __syncwarp();
    if (elect()) {
      asm volatile("cp.async.bulk.tensor.2d.global.shared::cta.bulk_group [%0, {%2,%3}], [%1];"
                   ::"l"(&mo), "r"(sb + 5 * SLOT + warp * 2048), "r"(sl * 64), "r"(tile * 128 + warp * 16) : "memory");
      asm volatile("cp.async.bulk.commit_group;" ::: "memory");
      asm volatile("cp.async.bulk.wait_group.read 0;" ::: "memory");
    }
    TS(8);
    TS_FLUSH();
  } else {
    const int h = warp & 3, bid = 1 + wg;
    const uint32_t ca = sb + (wg == 2 ? RING_BYTES : wg * CA_BYTES);
    const uint32_t up = sb + (wg == 2 ? UP_OFF : 2 * CA_BYTES + wg * 2 * U_BYTES);
    const int pair = is_mlp ? cta : NMLP + NEXP + min(w0, NEXP - 1);
    const bool spare = !is_mlp && w0 >= NEXP;
    const int cho = 2 * pair + (h >> 1);
    int chp = is_mlp ? cho : (spare ? 2 * (NMLP + 20 + 4 * (w0 - NEXP)) + (h >> 1) : cho - 2 * NEXP);
    uint32_t xr[14], ldo, ldp, dso, dsp;
    if (wg < 2) ln_load(P.x, min(cta, 127), warp, lane, xr);
    else {
#pragma unroll
      for (int i = 0; i < 6; i++)
        asm volatile("ld.global.nc.v2.u32 {%0,%1}, [%2];" : "=r"(xr[2 * i]), "=r"(xr[2 * i + 1]) : "l"((&P.Are)[i] + chp * 256 + (tid & 63) * 4));
    }
    asm volatile("ld.global.nc.u16 %0, [%1];" : "=r"(ldo) : "l"(P.logdt + cho));
    asm volatile("ld.global.nc.u16 %0, [%1];" : "=r"(ldp) : "l"(P.logdt + chp));
    asm volatile("ld.global.nc.u16 %0, [%1];" : "=r"(dso) : "l"(P.Dskip + cho));
    asm volatile("ld.global.nc.u16 %0, [%1];" : "=r"(dsp) : "l"(P.Dskip + chp));
    if (wg < 2) {
      BAR_SYNC(9 + wg, 160);
      if (cta < 128) ln_rows(P.scr->ab, xr, xr + 7, cta, tbuf, warp, lane);
      BAR_SYNC(4, 256);
      if (cta < 128) ln_store(P.scr->xT, cta, tbuf, tid);
      BAR_ARRIVE(5, 288);
      BAR_SYNC(4, 256);
    }
    {
      uint32_t par;
      float kv[12] = {};
      {
        const int tw = tid & 127, ml = tw & 63;

        uint2 pr[6];
#pragma unroll
        for (int i = 0; i < 6; i++) pr[i] = make_uint2(xr[2 * i], xr[2 * i + 1]);
        if (wg < 2) {
          mbar_wait(bars + 8 * wg, 0);
#pragma unroll
          for (int i = 0; i < 6; i++) pr[i] = lds64(ca + STG_BYTES + i * 1024 + tw * 8);
        }

        TS(50);
#pragma unroll 1
        for (int job = spare ? -3 : is_mlp; job < (spare ? 1 : 2); job++) {
         float kacc[24];
#pragma unroll
         for (int i = 0; i < 24; i++) kacc[i] = 0.f;
         pin<24>(kacc);
         const float dt = bfr(expf(lo16(job > 0 ? ldo : ldp)));
         const int pe = job == 0 && wg == 1 && cta < 128 ? 2 : 4;
#pragma unroll 1
         for (int p = spare ? 2 : 0; p < pe; p++) {
          const uint32_t stg = ca + (p & 1) * STG_BYTES;
          const uint32_t aA = stg + (tw >> 6) * 4096 + ml * 16, aB = stg + 16384 + (tw >> 6) * 3072 + ml * 16;
          float pf[6];
#pragma unroll
          for (int i = 0; i < 6; i++) pf[i] = __uint_as_float(__byte_perm(pr[i].x, pr[i].y, 0x1000 + p * 0x2200) & 0xffff0000u);
          const float l2 = (dt * pf[0]) * 1.4426950408889634f, tn = (dt * pf[1]) * 0.15915494309189535f;
          const float2 Bc = make_float2(pf[2], pf[3]), Cc = make_float2(pf[4], pf[5]);
          const float2 z1 = cexp2t(l2, tn), y1 = cexp2t(l2 * 256.f, tn * 256.f);
          const float2 z2 = csq(z1), z4 = csq(z2), z8 = csq(z4), z16 = csq(z8), z32 = csq(z16), z64 = csq(z32), z128 = csq(z64);
          const float2 y2 = csq(y1), by4 = cmul(Bc, csq(y2));
          {
            const uint32_t m1 = hmulp(z1), my = hmulp(y1), my2 = hmulp(y2);
            const uint2 q0 = hpair(Bc, cmul(Bc, z4)), q1 = hcmul(q0, hmulp(z2)), q2 = hcmul(q0, m1), q3 = hcmul(q1, m1);
            const uint2 q4 = hcmul(q0, my), q5 = hcmul(q1, my), q6 = hcmul(q0, my2), q7 = hcmul(q4, my2);
            const uint2 q8 = hpair(by4, cmul(by4, y1)), q9 = hcmul(q8, my2), q10 = hcmul(q9, my2);
            sts128(aB, q0.x, q1.x, q2.x, q3.x); sts128(aB + 6144, q0.y, q1.y, q2.y, q3.y);
            sts128(aB + 1024, q4.x, q5.x, q6.x, q7.x); sts128(aB + 7168, q4.y, q5.y, q6.y, q7.y);
            sts128(aB + 2048, q8.x, q9.x, q10.x, 0u); sts128(aB + 8192, q8.y, q9.y, q10.y, 0u);
          }
          {
            uint2 r[16];
            r[0] = hpair(Cc, cmul(Cc, z8));
            r[1] = hcmul(r[0], hmulp(z16));
            const uint32_t m32 = hmulp(z32), m64 = hmulp(z64), m128 = hmulp(z128);
#pragma unroll
            for (int i = 0; i < 2; i++) r[2 + i] = hcmul(r[i], m32);
#pragma unroll
            for (int i = 0; i < 4; i++) r[4 + i] = hcmul(r[i], m64);
#pragma unroll
            for (int i = 0; i < 8; i++) r[8 + i] = hcmul(r[i], m128);
#pragma unroll
            for (int c = 0; c < 4; c++) {
              sts128(aA + c * 1024, r[4 * c].x, r[4 * c + 1].x, r[4 * c + 2].x, r[4 * c + 3].x);
              sts128(aA + c * 1024 + 8192, r[4 * c].y, r[4 * c + 1].y, r[4 * c + 2].y, r[4 * c + 3].y);
            }
          }
          proxy_fence();
          wg_wait<0>();
          BAR_SYNC(bid, 128);
          const uint32_t dA = mkdesc(stg, 128), dB = mkdesc(stg + 16384, 128);
          wg_fence();
#pragma unroll
          for (int s = 0; s < 4; s++) {
            wg_ss48_pos(kacc, dA + s * 16, dB + s * 16);
            wg_ss48_neg(kacc, dA + 512 + s * 16, dB + 384 + s * 16);
          }
          wg_commit();
          TS(51 + 4 * max(job, 0) + p);
         }
         if (wg == 2 && job == (spare ? -3 : is_mlp)) BAR_SYNC(11, 160);
         par = get_parity(sb);
         __syncwarp();
         wg_wait<0>();
         pin<24>(kacc);
#pragma unroll
         for (int i = 0; i < 12; i++) kv[i] = dt * ((h >> 1) ? kacc[12 + i] : kacc[i]);
         if (ml == 0 && !spare) kv[0] += lo16(job ? dso : dsp);
         if (job <= 0) {
#pragma unroll
           for (int i = 0; i < 3; i++)
             stg_strong128(P.scr->kexp + (chp - 2 * NMLP + (spare ? 2 * NEXP - 40 : 0)) * 192 + i * 64 + ml, (__float_as_uint(kv[4 * i]) & ~1u) | par,
                           __float_as_uint(kv[4 * i + 1]), (__float_as_uint(kv[4 * i + 2]) & ~1u) | par, __float_as_uint(kv[4 * i + 3]));
           if (spare) {
             chp += 2;
             ldp = __ldg(reinterpret_cast<const uint16_t*>(P.logdt) + chp);
#pragma unroll
             for (int i = 0; i < 6; i++) pr[i] = __ldg(reinterpret_cast<const uint2*>((&P.Are)[i] + chp * 256 + ml * 4));
           } else {
             mbar_wait(bars + 8 * (3 + wg), 0);
#pragma unroll
             for (int i = 0; i < 6; i++) pr[i] = lds64(sb + 2 * CA_BYTES + 4 * U_BYTES + wg * 6144 + i * 1024 + tw * 8);
           }
         }
        }
        BAR_SYNC(bid, 128);
      }
#pragma unroll 1
      for (int c0 = 0; c0 < (is_mlp ? 2 : (spare ? 0 : 1)); c0++) {
        const int nc = 2 - c0;
        const uint32_t ub = c0 ? ca + U3_OFF : up;
        {
          const int tw = fresh_tw();
          if (c0) {
            mbar_wait(bars + 8 * B_U3, 0);
            const uint32_t fa = ca + F3_OFF + (tw & 63) * 16;
#pragma unroll
            for (int i = 0; i < 12; i++) kv[i] = 0.f;
#pragma unroll 1
            for (int part = 0; part <= (cta >= 40 && cta < 72); part++) {
              uint4 v[3];
              uint32_t bad = 0;
#pragma unroll
              for (int i = 0; i < 3; i++) { v[i] = lds128(fa + part * 3072 + i * 1024); bad |= tagchk(v[i].x, v[i].z, par); }
#pragma unroll 1
              for (int it = 0; __builtin_expect(tagbad(bad), 0) && it < POLL_LIMIT; it++) {
                bad = 0;
#pragma unroll
                for (int i = 0; i < 3; i++) {
                  v[i] = ldg_strong128(P.scr->kexp + (cta + part * (2 * NEXP - 40)) * 192 + i * 64 + (tw & 63));
                  bad |= tagchk(v[i].x, v[i].z, par);
                }
              }
#pragma unroll
              for (int i = 0; i < 3; i++) {
                kv[4 * i] += __uint_as_float(v[i].x); kv[4 * i + 1] += __uint_as_float(v[i].y);
                kv[4 * i + 2] += __uint_as_float(v[i].z); kv[4 * i + 3] += __uint_as_float(v[i].w);
              }
            }
            __syncwarp();
          }
          const int tq = tw & 3, b0 = (h & 1) * 16 + ((tw & 31) >> 2);
          const uint32_t lin = ca + LIN_OFF + (h >> 1) * LIN_BYTES;
#pragma unroll
        for (int i = 0; i < 6; i++) {
          const uint64_t BASE[6] = {0x000C000400080000ull, 0x001C001400180010ull, 0x070C060C04040400ull,
                                    0x07100610040C0408ull, 0x06040A0C090C080Cull, 0x06080600098C088Cull};
          const uint32_t STRD[6] = {0x20202020u, 0x20202020u, 0x08081010u, 0x08081010u, 0x00040404u, 0x00000404u};
          const uint32_t st = (STRD[i] >> (8 * tq)) & 0xffu, a = lin + ((uint32_t)(BASE[i] >> (16 * tq)) & 0xffffu) + b0 * st;
          sts32(a, __float_as_uint(kv[(i >> 1) * 4 + (i & 1)]));
          sts32(a + 8 * st, __float_as_uint(kv[2 + (i >> 1) * 4 + (i & 1)]));
        }
        }
        if (!c0) mbar_wait(bars + 8 * B_U, 0);
        BAR_SYNC(bid, 128);
        TS(c0 ? 12 : 19);
#pragma unroll 1
        for (int c = 0; c < nc; c++) {
          const int tw = fresh_tw(), ln = tw & 31;
          const int m = min(25 + 25 * h + ln, 127);
          const int role = 0, blk = tw;
          const uint32_t lin = ca + LIN_OFF + c * LIN_BYTES, cb = ca + c * CH_BYTES, ua = ub + c * U_BYTES + (127 - blk) * 32;
          uint4 w[5];
          {
            const uint32_t u0 = ua ^ ((ua >> 3) & 16), u1 = (ua + 32) ^ (((ua + 32) >> 3) & 16), u2 = (ua + 80) ^ (((ua + 64) >> 3) & 16);
            w[0] = lds128(u2); w[1] = lds128(u1); w[2] = lds128(u1 ^ 16); w[3] = lds128(u0); w[4] = lds128(u0 ^ 16);
          }
          const float4 t2 = lds128f(lin + (260 + 4 * min(m, 63)) * 4);
          const uint2 t3 = lds64(lin + (388 + 2 * m) * 4);
          const float k1024 = ldsf(lin + 515 * 4);
          float v[5];
#pragma unroll
          for (int i = 0; i < 5; i++) {
            const int x = tw + 128 * i - 16, d = x - 256, q = 256 + ((d + ((d >> 1) & 1)) >> 1);
            v[i] = ldsf(lin + 4 * (x < 256 ? max(x, 0) : (q < 384 ? q : 387)));
          }
          const uint32_t cw = pack2(k1024, k1024);
          uint32_t tw4[3][4];
          tw4[0][0] = m < 32 ? 0u : (m > 63 ? cw : pack2(t2.x, t2.y));
          tw4[1][0] = m < 32 ? 0u : (m > 63 ? cw : pack2(t2.z, t2.w));
          tw4[2][0] = m < 64 ? 0u : pack2(__uint_as_float(t3.x) - lo16(cw), __uint_as_float(t3.y) - lo16(cw));
#pragma unroll
          for (int k = 0; k < 3; k++)
#pragma unroll
            for (int j = 1; j < 4; j++) tw4[k][j] = __shfl_up_sync(0xffffffffu, tw4[k][0], j);
#pragma unroll
          for (int i = 0; i < 5; i++) {
            const bool on = i == 0 ? tw >= 16 : (i == 4 ? tw < 19 : true);
            const uint32_t pw = pack2(on ? v[i] : 0.f, 0.f);
            if (i < 4 || tw < 32) { sts16(cb + TP_OFF + (tw + 128 * i) * 4, pw); sts16(cb + TP_OFF + (tw + 128 * i) * 4 + 6, pw); }
          }
          if (ln >= 3 && ln < 28) {
#pragma unroll
            for (int k = 0; k < 3; k++) sts128(cb + T2A_OFF + k * TT_BYTES + (127 - m) * 16, tw4[k][0], tw4[k][1], tw4[k][2], tw4[k][3]);
          }
          if (tw < 4) sts128(cb + V2_OFF - 64 + tw * 16, 0u, 0u, 0u, 0u);
          if (role < 3) {
            float S[34];
            auto el = [&](int e) { const uint32_t ww = (&w[e >> 3].x)[(e >> 1) & 3]; return (e & 1) ? hi16(ww) : lo16(ww); };
            S[21] = 0.f;
#pragma unroll
            for (int k = 22; k < 34; k++) S[k] = S[k - 1] + el(k + 3);
#pragma unroll
            for (int k = 20; k >= 10; k--) S[k] = S[k + 1] - el(k + 4);
            const uint32_t key = vkey(blk);
#pragma unroll
            for (int cc = 0; cc < 4; cc++) {
              uint32_t v2[4];
#pragma unroll
              for (int n = 0; n < 4; n++) {
                const int i = 2 * cc + (n >> 1) + (n & 1) * 8;
                v2[n] = pack2(S[i + 18] - S[i + 15], S[i + 15] - S[i + 10]);
              }
              if (blk < 96) sts128(cb + V2_OFF + blk * 64 + ((cc * 16) ^ key), v2[0], v2[1], v2[2], v2[3]);
            }
            if (role < 2) {
#pragma unroll
              for (int k = 9; k >= 0; k--) S[k] = S[k + 1] - el(k + 4);
#pragma unroll
              for (int cc = 0; cc < 4; cc++) {
                uint32_t v3[4];
#pragma unroll
                for (int n = 0; n < 4; n++) {
                  const int i = 2 * cc + (n >> 1) + (n & 1) * 8;
                  v3[n] = pack2(S[i + 16] - S[i + 9], S[i + 9] - S[i]);
                }
                if (blk < 64) sts128(cb + V3_OFF + blk * 64 + ((cc * 16) ^ key), v3[0], v3[1], v3[2], v3[3]);
              }
            }
          }
        }
        proxy_fence();
        BAR_SYNC(bid, 128);
        TS(c0 ? 16 : 11);
#pragma unroll 1
        for (int c = 0; c < nc; c++) {
          const int ln = fresh_tw() & 31, gg = ln >> 2, tq = ln & 3;
          const uint32_t gq = (gg >> 1) * 16, gl = (gg & 1) * 8;
          const uint32_t o0 = tq * 64 + (gq ^ vkey(tq)) + gl, o4 = (tq + 4) * 64 + (gq ^ vkey(tq + 4)) + gl;
          const uint32_t om1 = (tq - 1) * 64 + (gq ^ vkey(tq - 1)) + gl + 4, o3 = (tq + 3) * 64 + (gq ^ vkey(tq + 3)) + gl + 4;
          const uint32_t cb = ca + c * CH_BYTES;
          if (is_mlp && c == 1 && h == 0 && elect()) {
            const bool two = cta >= 40 && cta < 72;
            expect_tx(bars + 8 * B_U3, U_COPY + (two ? 6144 : 3072));
            if (two) bulk_load(ca + F3_OFF + 3072, P.scr->kexp + (cta + 2 * NEXP - 40) * 192, 3072, bars + 8 * B_U3);
            bulk_load(ca + U3_OFF, P.scr->xT + (2 * NMLP + cta) * 276, U_COPY, bars + 8 * B_U3);
            bulk_load(ca + F3_OFF, P.scr->kexp + cta * 192, 3072, bars + 8 * B_U3);
          }
          __syncwarp();
          float d[64];
          const uint32_t pa = cb + TP_OFF + (gg - 2 * tq + 8) * 4 + h * 512;
          const uint32_t v2b = cb + V2_OFF + h * 512, v3b = cb + V3_OFF + h * 512;
          const uint32_t dU = mkdesc(ub + c * U_BYTES, 16), d2 = mkdesc(cb + T2A_OFF, TT_BYTES), d3 = mkdesc(cb + T3_OFF, 64);
          uint32_t A[4][4];
          auto ld2 = [&](int q) {
            const uint2 a = lds64(v2b + q * 2048 + o0), b = lds64(v2b + q * 2048 + o4);
            A[0][0] = a.x; A[0][1] = a.y; A[0][2] = lds32(v2b + q * 2048 + om1); A[0][3] = cpy(a.x);
            A[1][0] = b.x; A[1][1] = b.y; A[1][2] = lds32(v2b + q * 2048 + o3); A[1][3] = cpy(b.x);
          };
          auto ld3 = [&](int q) {
            const uint2 e = lds64(v3b + q * 2048 + o0), f = lds64(v3b + q * 2048 + o4);
            A[2][0] = e.x; A[2][1] = e.y; A[2][2] = f.x; A[2][3] = f.y;
          };
#define AF(i) A[i][0], A[i][1], A[i][2], A[i][3]
#define WIDEN(n) { wg_wait<0>(); _Pragma("unroll") for (int i = (n) - 16; i < (n); i++) d[i] = 0.f; pin<(n)>(d); }
          ld2(2); ld3(1);
          wg_fence();
          wg_rs32_init(d, AF(0), d2 + 64); wg_rs32(d, AF(1), d2 + 68); wg_rs32(d, AF(2), d3 + 32);
          wg_commit();
          ld2(1); ld3(0);
          WIDEN(32)
          wg_fence();
          wg_rs64(d, AF(0), d2 + 32); wg_rs64(d, AF(1), d2 + 36); wg_rs64(d, AF(2), d3);
          wg_commit();
          ld2(0);
          A[2][0] = lds32(pa + 2048 + 32); A[2][1] = lds32(pa + 2048 + 64); A[2][2] = lds32(pa + 2048);
#pragma unroll
          for (int i = 0; i < 3; i++) A[2][i] = h ? 0u : A[2][i];
          A[2][3] = cpy(A[2][0]); A[3][0] = cpy(0u); A[3][1] = cpy(0u); A[3][2] = cpy(A[2][1]); A[3][3] = cpy(0u);
          WIDEN(48)
          wg_fence();
          wg_rs96(d, AF(0), d2); wg_rs96(d, AF(1), d2 + 4); wg_rs96_u(d, AF(2), dU + 64); wg_rs96_u(d, AF(3), dU + 66);
          wg_commit();
#pragma unroll
          for (int bt = 0; bt < 4; bt++) {
            A[0][0] = lds32(pa + bt * 128 + 32); A[0][1] = lds32(pa + bt * 128 + 64); A[0][2] = lds32(pa + bt * 128);
            A[1][0] = lds32(pa + bt * 128 + 96); A[1][1] = lds32(pa + bt * 128 + 128);
            A[0][3] = cpy(A[0][0]); A[1][2] = cpy(A[0][1]); A[1][3] = cpy(A[1][0]);
            if (bt == 0) WIDEN(64)
            if (bt >= 2) wg_wait<1>();
            wg_fence();
            wg_rs128_u(d, AF(0), dU + 4 * bt); wg_rs128_u(d, AF(1), dU + 4 * bt + 2);
            wg_commit();
          }
          wg_wait<0>();
          pin<64>(d);
          TS(28 + c + 2 * c0);
          BAR_SYNC(bid, 128);
          const uint32_t red = cb + ln * 8;
#pragma unroll
          for (int j = 1; j < 16; j++)
            if (j & 3) sts64(red + h * 3072 + (((j & 3) - 1) * 4 + (j >> 2)) * 256, pack2(d[60 - 4 * j], d[61 - 4 * j]), pack2(d[62 - 4 * j], d[63 - 4 * j]));
          BAR_SYNC(bid, 128);
          uint2 rv[3][4];
#pragma unroll
          for (int k = 0; k < 3; k++) {
            const int h2 = (h + 3 - k) & 3;
            const uint32_t ra = red + h2 * 3072 + k * 1024 - (h2 > h ? 256 : 0);
            rv[k][0] = make_uint2(0u, 0u);
            if (h2 < h) rv[k][0] = lds64(ra);
#pragma unroll
            for (int a = 1; a < 4; a++) rv[k][a] = lds64(ra + a * 256);
          }
          const int ch = c0 ? 2 * NMLP + cta : 2 * pair + c;
          uint2* sp = P.scr->s + (h * DM + ch) * 32 + (((3 - tq) * 8 + gg) ^ (((ch >> 1) & 3) * 4));
#pragma unroll
          for (int a = 0; a < 4; a++) {
            const uint32_t ex = hadd2(hadd2(rv[0][a].x, rv[1][a].x), rv[2][a].x), ey = hadd2(hadd2(rv[0][a].y, rv[1][a].y), rv[2][a].y);
            const float r0 = d[60 - 16 * a] + lo16(ex), r1 = d[61 - 16 * a] + hi16(ex), r2 = d[62 - 16 * a] + lo16(ey), r3 = d[63 - 16 * a] + hi16(ey);
            stg_strong64(sp + a * (4 * DM * 32), pack_tag(r1, r3, par), pack_tag(r0, r2, par));
          }
          stg_hint(P.scr->hints + ch * 4 + h, par, ln);
          TS(13 + c + 2 * c0);
        }
      }
    }
    TS_FLUSH();
  }
}

__device__ __forceinline__ float blk_sum(float v, float* red) {
  for (int o = 16; o; o >>= 1) v += shx(v, o);
  __syncthreads();
  if ((threadIdx.x & 31) == 0) red[threadIdx.x >> 5] = v;
  __syncthreads();
  float s = 0.f;
  for (int i = 0; i < 14; i++) s += red[i];
  return s;
}
__device__ __forceinline__ float ln_plain(float v, float* red) {
  const float mean = blk_sum(v, red) * (1.f / DM), var = blk_sum((v - mean) * (v - mean), red) * (1.f / DM);
  return bfr(bfr(v - bfr(mean)) / bfr(sqrtf(bfr(bfr(var) + 1e-5f))));
}
__global__ void __launch_bounds__(DM) fb_prep(const Params P) {
  __shared__ float red[14];
  float* xn = reinterpret_cast<float*>(P.scr->part);
  if (blockIdx.x < LSEQ) {
    xn[blockIdx.x * DM + threadIdx.x] = ln_plain(__bfloat162float(P.x[blockIdx.x * DM + threadIdx.x]), red);
    return;
  }
  const int d = blockIdx.x - LSEQ;
  const float dt = bfr(expf(__bfloat162float(P.logdt[d])));
  for (int l = threadIdx.x; l < LSEQ; l += DM) {
    const float lf = bfr((float)l);
    float k = 0.f;
    for (int n = d * 256; n < d * 256 + 256; n++) {
      const float2 w = cmul(make_float2(__bfloat162float(P.Cre[n]), __bfloat162float(P.Cim[n])),
                            make_float2(dt * __bfloat162float(P.Bre[n]), dt * __bfloat162float(P.Bim[n])));
      float sn, cs;
      sincosf(dt * __bfloat162float(P.Aim[n]) * lf, &sn, &cs);
      k += expf(dt * __bfloat162float(P.Are[n]) * lf) * (w.x * cs - w.y * sn);
    }
    xn[LSEQ * DM + l * DM + d] = k;
  }
}
__global__ void __launch_bounds__(DM) fb_main(const Params P, __nv_bfloat16* out) {
  __shared__ float red[14], y[DM], h[FF];
  const float* xn = reinterpret_cast<const float*>(P.scr->part);
  const int l = blockIdx.x, d = threadIdx.x;
  y[d] = ln_plain(xn[l * DM + d], red);
  __syncthreads();
  for (int f = d; f < FF; f += DM) {
    float u = __bfloat162float(P.b1[f]);
    for (int k = 0; k < DM; k++) u = fmaf(y[k], __bfloat162float(P.w1[k * FF + f]), u);
    h[f] = bfr(0.5f * u * (1.f + tanhf(u * fmaf(u * u, 0.035677408136300125f, 0.7978845608028654f))));
  }
  __syncthreads();
  float v = __bfloat162float(P.b2[d]), s = xn[l * DM + d] * __bfloat162float(P.Dskip[d]);
  for (int f = 0; f < FF; f++) v = fmaf(h[f], __bfloat162float(P.w2[f * DM + d]), v);
  for (int j = 0; j <= l; j++) s = fmaf(xn[LSEQ * DM + j * DM + d], xn[(l - j) * DM + d], s);
  out[l * DM + d] = __float2bfloat16(__bfloat162float(P.x[l * DM + d]) + s * v / (1.f + expf(-v)));
}

typedef CUresult (*EncodeFn)(CUtensorMap*, CUtensorMapDataType, cuuint32_t, void*, const cuuint64_t*, const cuuint64_t*, const cuuint32_t*,
                             const cuuint32_t*, CUtensorMapInterleave, CUtensorMapSwizzle, CUtensorMapL2promotion, CUtensorMapFloatOOBfill);

}

extern "C" void kernel_launch(void* const* d_in, const int* in_sizes, int n_in, void* d_out, int out_size) {
  (void)in_sizes; (void)n_in; (void)out_size;
  static EncodeFn enc = nullptr;
  static int grid = 0;
  static Scratch* scr = nullptr;
  if (!scr) {
    void* fn = nullptr;
    cudaDriverEntryPointQueryResult qr;
    cudaGetDriverEntryPoint("cuTensorMapEncodeTiled", &fn, cudaEnableDefault, &qr);
    enc = (EncodeFn)fn;
    cudaFuncSetAttribute(s4_mixer_kernel, cudaFuncAttributeMaxDynamicSharedMemorySize, SMEM_BYTES);
    cudaGetSymbolAddress((void**)&scr, g_scr);
    int dev = 0, sms = 0;
    cudaGetDevice(&dev);
    cudaDeviceGetAttribute(&sms, cudaDevAttrMultiProcessorCount, dev);
    int occ = 0;
    cudaOccupancyMaxActiveBlocksPerMultiprocessor(&occ, s4_mixer_kernel, 512, SMEM_BYTES);
    grid = (enc && occ >= 1 && sms >= 132) ? 132 : 0;
  }
  typedef const __nv_bfloat16* bp;
  Params P{(bp)d_in[0], (bp)d_in[10], (bp)d_in[1], (bp)d_in[2], (bp)d_in[3], (bp)d_in[4], (bp)d_in[5], (bp)d_in[6], (bp)d_in[7],
           (bp)d_in[8], (bp)d_in[11], (bp)d_in[13], (bp)d_in[12], scr};
  if (!grid) {
    fb_prep<<<LSEQ + DM, DM, 0, cudaStreamPerThread>>>(P);
    fb_main<<<LSEQ, DM, 0, cudaStreamPerThread>>>(P, (__nv_bfloat16*)d_out);
    return;
  }
  CUtensorMap mx, mw1, mw2, mo;
  const cuuint32_t one[3] = {1, 1, 1};
  {
    cuuint64_t dim[2] = {DM, LSEQ}, str[1] = {DM * 2};
    cuuint32_t box[2] = {64, 128};
    enc(&mx, CU_TENSOR_MAP_DATA_TYPE_BFLOAT16, 2, d_in[0], dim, str, box, one, CU_TENSOR_MAP_INTERLEAVE_NONE, CU_TENSOR_MAP_SWIZZLE_128B,
        CU_TENSOR_MAP_L2_PROMOTION_L2_128B, CU_TENSOR_MAP_FLOAT_OOB_FILL_NONE);
  }
  {
    cuuint64_t dim[3] = {64, DM, FF / 64}, str[2] = {FF * 2, 128};
    cuuint32_t box[3] = {64, 64, 4};
    enc(&mw1, CU_TENSOR_MAP_DATA_TYPE_BFLOAT16, 3, d_in[10], dim, str, box, one, CU_TENSOR_MAP_INTERLEAVE_NONE, CU_TENSOR_MAP_SWIZZLE_128B,
        CU_TENSOR_MAP_L2_PROMOTION_L2_128B, CU_TENSOR_MAP_FLOAT_OOB_FILL_NONE);
  }
  {
    cuuint64_t dim[2] = {DM, FF}, str[1] = {DM * 2};
    cuuint32_t box[2] = {64, 256};
    enc(&mw2, CU_TENSOR_MAP_DATA_TYPE_BFLOAT16, 2, d_in[12], dim, str, box, one, CU_TENSOR_MAP_INTERLEAVE_NONE, CU_TENSOR_MAP_SWIZZLE_128B,
        CU_TENSOR_MAP_L2_PROMOTION_L2_128B, CU_TENSOR_MAP_FLOAT_OOB_FILL_NONE);
  }
  {
    cuuint64_t dim[2] = {DM, LSEQ}, str[1] = {DM * 2};
    cuuint32_t box[2] = {64, 16};
    enc(&mo, CU_TENSOR_MAP_DATA_TYPE_BFLOAT16, 2, d_out, dim, str, box, one, CU_TENSOR_MAP_INTERLEAVE_NONE, CU_TENSOR_MAP_SWIZZLE_128B,
        CU_TENSOR_MAP_L2_PROMOTION_NONE, CU_TENSOR_MAP_FLOAT_OOB_FILL_NONE);
  }
  s4_mixer_kernel<<<grid, 512, SMEM_BYTES, cudaStreamPerThread>>>(P, mx, mw1, mw2, mo);
}
```
